```python
import torch

def _softmax(x, axis=-1):
    return torch.softmax(x, dim=axis)
def _gelu(x):
    return torch.nn.functional.gelu(x, approximate="tanh")
def _silu(x):
    return torch.nn.functional.silu(x)
def _sigmoid(x):
    return torch.sigmoid(x)
def _layernorm(x, axis=-1, eps=1e-5):
    m = x.mean(dim=axis, keepdim=True)
    v = x.var(dim=axis, keepdim=True, unbiased=False)
    return (x - m) / torch.sqrt(v + eps)
def _scatter_add(tgt, idx, src, axis=0):
    return tgt.clone().index_add_(axis, idx, src)
def _segment_sum(src, seg, n):
    out = torch.zeros((n,) + src.shape[1:], dtype=src.dtype)
    return out.index_add_(0, seg, src)
def _pad(x, pw):
    flat = tuple(v for pair in reversed(pw) for v in pair)
    return torch.nn.functional.pad(x, flat)

kernel_name = 'recurrent_scan__ssm_conv_s4__glu_gated_glu__prompt'

def setup_inputs():

    _w = (lambda a: (lambda t: t.to(torch.bfloat16) if t.is_floating_point() else t)(torch.as_tensor(a)))
    def _A_setup():
        B, L, D, N = 1, 2048, 512, 128
        A_re = -(lambda _x: torch.exp(torch.as_tensor(_x)))((lambda *s: torch.randn(*s, dtype=torch.bfloat16) * 6.4)(D, N))
        A_im = torch.pi * (lambda *s: torch.randn(*s, dtype=torch.bfloat16) * 0.05)(D, N)
        B_re = (lambda *s: torch.randn(*s, dtype=torch.bfloat16) * 0.1)(D, N)
        B_im = (lambda *s: torch.randn(*s, dtype=torch.bfloat16) * 0.1)(D, N)
        C_re = (lambda *s: torch.randn(*s, dtype=torch.bfloat16) * 0.1)(D, N)
        C_im = (lambda *s: torch.randn(*s, dtype=torch.bfloat16) * 0.1)(D, N)
        log_dt = (lambda *s: torch.randn(*s, dtype=torch.bfloat16) * 0.05)(D) * 0.5 - 4.0
        Dskip = (lambda *s: torch.randn(*s, dtype=torch.bfloat16) * 0.05)(D)
        return {
            "u": _w((lambda *s: torch.randn(*s, dtype=torch.bfloat16) * 0.05)(B, L, D)),
            "A_re": _w(A_re),
            "A_im": _w(A_im),
            "B_re": _w(B_re),
            "B_im": _w(B_im),
            "C_re": _w(C_re),
            "C_im": _w(C_im),
            "log_dt": _w(log_dt),
            "Dskip": _w(Dskip),
        }
    _A_in = _A_setup()

    def _B_setup():
        B, S, D, F = 1, 2048, 512, 1376
        return {
            "x": _w((lambda *s: torch.randn(*s, dtype=torch.bfloat16) * 0.05)(B, S, D)),
            "w_gate": _w((lambda *s: torch.randn(*s, dtype=torch.bfloat16) * 0.05)(D, F)),
            "w_up": _w((lambda *s: torch.randn(*s, dtype=torch.bfloat16) * 0.05)(D, F)),
            "w_down": _w((lambda *s: torch.randn(*s, dtype=torch.bfloat16) * 0.05)(F, D)),
        }
    _B_in = _B_setup()

    return {
        "A_u": _A_in["u"],
        "A_A_re": _A_in["A_re"],
        "A_A_im": _A_in["A_im"],
        "A_B_re": _A_in["B_re"],
        "A_B_im": _A_in["B_im"],
        "A_C_re": _A_in["C_re"],
        "A_C_im": _A_in["C_im"],
        "A_log_dt": _A_in["log_dt"],
        "A_Dskip": _A_in["Dskip"],
        "B_x": _B_in["x"],
        "B_w_gate": _B_in["w_gate"],
        "B_w_up": _B_in["w_up"],
        "B_w_down": _B_in["w_down"],
    }

def reference(A_u, A_A_re, A_A_im, A_B_re, A_B_im, A_C_re, A_C_im, A_log_dt, A_Dskip, B_x, B_w_gate, B_w_up, B_w_down):
    def _A_ref(u, A_re, A_im, B_re, B_im, C_re, C_im, log_dt, Dskip):
        Bsz, L, D = u.shape
        dt = torch.exp(log_dt)[:, None]
        A = A_re + 1j * A_im
        Bc = B_re + 1j * B_im
        Cc = C_re + 1j * C_im
        logdA = dt * A
        dB = dt * Bc
        l = (lambda x, dt: x.to(dt))(torch.arange(L), A_re.dtype)
        P = torch.exp(logdA[:, :, None] * l[None, None, :])
        K = torch.einsum("dn,dnl,dn->dl", Cc, P, dB).real
        L2 = 2 * L
        Kp = _pad(K, ((0, 0), (0, L)))
        up = (lambda x, *d: x.permute(*d))(u, 0, 2, 1)
        up = _pad(up, ((0, 0), (0, 0), (0, L)))
        Kf = (lambda x, axes=(-2,-1): torch.fft.rfft2(x.float(), dim=axes))(Kp[:, None, :], axes=(-2, -1))
        Uf = (lambda x, axes=(-2,-1): torch.fft.rfft2(x.float(), dim=axes))(up[:, :, None, :], axes=(-2, -1))
        Yf = Uf * Kf[None, :, :, :]
        y = (lambda x, s, axes=(-2,-1): torch.fft.irfft2(x, s=s, dim=axes).to(torch.bfloat16))(Yf, (1, L2), axes=(-2, -1))[:, :, 0, :L]
        y = (lambda x, *d: x.permute(*d))(y, 0, 2, 1) + u * Dskip[None, None, :]
        return y

    def _B_ref(x, w_gate, w_up, w_down):
        g = torch.einsum("bsd,df->bsf", x, w_gate)
        u = torch.einsum("bsd,df->bsf", x, w_up)
        h = _sigmoid(g) * u
        return torch.einsum("bsf,fd->bsd", h, w_down)

    x = A_u
    xn = _layernorm(x, axis=-1)
    s = _A_ref(xn, A_A_re, A_A_im, A_B_re, A_B_im, A_C_re, A_C_im, A_log_dt, A_Dskip)
    g = _silu(_B_ref(xn, B_w_gate, B_w_up, B_w_down))
    return x + s * g
```

```cpp
#include <cuda_runtime.h>
#include <cuda_bf16.h>
#include <cuda.h>
#include <stdint.h>

namespace {

constexpr int KSPLIT = 320;
constexpr int SEQ = 2048, DM = 512, NST = 128, FF = 1376, FP = 1408;

__device__ __align__(1024) __nv_bfloat16 g_xnT[DM * SEQ];
__device__ __align__(1024) __nv_bfloat16 g_sT[DM * SEQ];
__device__ __align__(1024) __nv_bfloat16 g_h[SEQ * FP];
__device__ __align__(128) uint2 g_stats[SEQ];
__device__ __align__(128) uint2 g_cs[2][2 * FP];
__device__ __align__(128) unsigned g_cnt[40 * 32];
constexpr int CNT_TICKET = 0, CNT_LN = 1, CNT_H = 10, CNT_S = 26;
#define TSTAMP(i) do {} while (0)

constexpr uint32_t SLOT = 16384;
constexpr uint32_t OFF_A = 0;
constexpr uint32_t OFF_B = 49152;
constexpr uint32_t BST = 24576, BTX = 22528;
constexpr uint32_t OFF_CB = 147456;
constexpr uint32_t CB_B3 = 0, CB_H = 3600, CB_Z = 24912, CB_U = 29008, CBS = 33648;
constexpr uint32_t U_JS = 2320;
constexpr uint32_t KG_TAB = 4608;
constexpr uint32_t OFF_KC = OFF_CB + 3072;
constexpr uint32_t OFF_R = OFF_CB + 2 * CBS;
constexpr uint32_t RCH = 2752;
constexpr uint32_t OFF_MA = OFF_R + 4 * RCH;
static_assert(OFF_MA >= OFF_CB + 16 * KG_TAB, "scratch");
constexpr uint32_t OFF_CS = OFF_MA + 2048;
constexpr uint32_t OFF_RED = OFF_CS + 2208;
constexpr uint32_t OFF_STAT = OFF_RED + 640;
constexpr uint32_t OFF_CX = OFF_R + 2 * RCH, OFF_CS2 = OFF_CX + 6144;
static_assert(OFF_CS2 + 4096 <= OFF_STAT, "cx");
constexpr uint32_t OFF_BAR = OFF_STAT + 512;
constexpr uint32_t OFF_EPOCH = OFF_BAR + 496;
constexpr uint32_t OFF_DBG = OFF_EPOCH + 16;
constexpr uint32_t SMEM_BYTES = OFF_DBG + 256;
static_assert(SMEM_BYTES <= 232448, "smem");

constexpr int B_FULLA = 0, B_EMPTYA = 3, B_FULLB = 6, B_EMPTYB = 10, B_FULL2 = 14  , B_REL2 = 27  , B_TF = 34, B_CF3 = 35, B_EPI1 = 36,
              B_STG = 37, B_CF = 38  , B_UF = 41  , B_TB = 45  , B_XF = 48, B_SF = 49, B_XCF = 50, B_XCR = 51,
              B_XCL = 52, B_EPOCH = 53, B_KG = 54, B_CD = 55  , B_KC = 58, B_G1E = 59, B_TZ = 60  , B_COUNT = 62;
__device__ __forceinline__ uint32_t bar_count(int i) {
  return (i >= B_EMPTYB && i < B_FULL2) ? 10u : i == B_CF3 ? 8u : i == B_TF ? 2u : (i == B_TB + 1 || i == B_TB + 2) ? 6u : i == B_KG ? 16u : (i == B_EPI1 || i == B_STG) ? 3u
       : ((i >= B_CF && i < B_UF) || (i >= B_TB && i < B_XF) || i == B_XCL || i >= B_G1E) ? 4u
       : ((i >= B_EMPTYA && i < B_FULLB) || (i >= B_FULL2 && i < B_REL2)) ? 2u : 1u;
}

__host__ __device__ constexpr uint32_t SL(int i) { return (uint32_t)i * SLOT; }
constexpr uint32_t OFF_B1S = (OFF_CB + CBS + 1023) & ~1023u;
static_assert(OFF_B1S + 2 * SLOT <= OFF_CB + 2 * CBS, "b1s");
constexpr uint32_t XA = OFF_CB, XB = OFF_CB + SLOT;
__host__ __device__ constexpr uint32_t wd_slot(int i) {
  return i == 0 ? SL(2) : i == 1 ? SL(3) : i == 2 ? SL(0) : i == 3 ? SL(4) : i == 4 ? SL(5) : i == 5 ? SL(6)
       : i == 6 ? SL(3) : i == 7 ? SL(0) : i == 8 ? SL(4) : i == 9 ? SL(5) : i == 10 ? SL(5) + 8192 : i == 11 ? SL(6) : SL(6) + 8192;
}
__host__ __device__ constexpr uint32_t h_slot(int i) {
  return i == 0 ? SL(1) : i == 1 ? SL(7) : i == 2 ? SL(8) : i == 3 ? XA : i == 4 ? XB : i == 5 ? SL(2)
       : i == 6 ? SL(1) : i == 7 ? SL(7) : i == 8 ? SL(8) : i == 9 ? XA : i == 10 ? XB : i == 11 ? OFF_B1S : OFF_B1S + SLOT;
}
constexpr uint32_t OFF_XT = SL(1), OFF_ST = SL(2), OFF_XC = SL(3), OFF_XL = SL(0);

__device__ __forceinline__ void mbar_init(uint32_t bar, uint32_t cnt) { asm volatile("mbarrier.init.shared::cta.b64 [%0], %1;" ::"r"(bar), "r"(cnt) : "memory"); }
__device__ __forceinline__ void mbar_expect_tx(uint32_t bar, uint32_t bytes) { asm volatile("mbarrier.arrive.expect_tx.shared::cta.b64 _, [%0], %1;" ::"r"(bar), "r"(bytes) : "memory"); }
__device__ __forceinline__ void mbar_arrive(uint32_t bar) { asm volatile("mbarrier.arrive.shared::cta.b64 _, [%0];" ::"r"(bar) : "memory"); }
__device__ __forceinline__ void mbar_arrive_n(uint32_t cbar, uint32_t n) { asm volatile("mbarrier.arrive.shared::cluster.b64 _, [%0], %1;" ::"r"(cbar), "r"(n) : "memory"); }
__device__ __forceinline__ uint32_t mapa(uint32_t a, uint32_t cta) { uint32_t r; asm volatile("mapa.shared::cluster.u32 %0, %1, %2;" : "=r"(r) : "r"(a), "r"(cta)); return r; }
__device__ __forceinline__ void mbar_arrive_remote(uint32_t cbar) { asm volatile("mbarrier.arrive.shared::cluster.b64 _, [%0];" ::"r"(cbar) : "memory"); }
__device__ __forceinline__ void mbar_wait(uint32_t bar, uint32_t parity) {
  asm volatile("{\n.reg .pred p;\n.reg .u32 c;\nmov.u32 c, 0;\nLW_%=:\n"
               "mbarrier.try_wait.parity.shared::cta.b64 p, [%0], %1;\n@p bra LD_%=;\n"
               "add.u32 c, c, 1;\nsetp.lt.u32 p, c, 200000;\n@p bra LW_%=;\nLD_%=:\n}" ::"r"(bar), "r"(parity) : "memory");
}
__device__ __forceinline__ void mbar_wait_cluster(uint32_t bar, uint32_t parity) {
  asm volatile("{\n.reg .pred p;\n.reg .u32 c;\nmov.u32 c, 0;\nLW_%=:\n"
               "mbarrier.try_wait.parity.acquire.cluster.shared::cta.b64 p, [%0], %1;\n@p bra LD_%=;\n"
               "add.u32 c, c, 1;\nsetp.lt.u32 p, c, 200000;\n@p bra LW_%=;\nLD_%=:\n}" ::"r"(bar), "r"(parity) : "memory");
}
__device__ __forceinline__ void poll_ge(const unsigned* p, unsigned target) {
  asm volatile("{\n.reg .pred p;\n.reg .u32 c, v;\n.reg .s32 d;\nmov.u32 c, 0;\nLW_%=:\n"
               "ld.acquire.gpu.global.u32 v, [%0];\nsub.s32 d, v, %1;\nsetp.ge.s32 p, d, 0;\n@p bra LD_%=;\n"
               "nanosleep.u32 20;\nadd.u32 c, c, 1;\nsetp.lt.u32 p, c, 400000;\n@p bra LW_%=;\nLD_%=:\n}" ::"l"(p), "r"(target) : "memory");
}
__device__ __forceinline__ void st_tag(uint2* p, uint32_t x, uint32_t y) {
  asm volatile("{\n.reg .b64 v;\nmov.b64 v, {%1, %2};\nst.relaxed.gpu.global.b64 [%0], v;\n}" ::"l"(p), "r"(x), "r"(y) : "memory");
}
__device__ __forceinline__ uint4 ld_tag2(const uint2* p) {
  uint4 v;
  asm volatile("{\n.reg .b64 a, b;\nld.relaxed.gpu.global.v2.b64 {a, b}, [%4];\nmov.b64 {%0, %1}, a;\nmov.b64 {%2, %3}, b;\n}"
               : "=r"(v.x), "=r"(v.y), "=r"(v.z), "=r"(v.w) : "l"(p) : "memory");
  return v;
}
__device__ __forceinline__ void red_relaxed(unsigned* p) { asm volatile("red.relaxed.gpu.global.add.u32 [%0], 1;" ::"l"(p) : "memory"); }
__device__ __forceinline__ void red_release(unsigned* p) { asm volatile("red.release.gpu.global.add.u32 [%0], 1;" ::"l"(p) : "memory"); }
__device__ __forceinline__ void fence_async_smem() { asm volatile("fence.proxy.async.shared::cta;" ::: "memory"); }
__device__ __forceinline__ void bar_sync(int id, int n) { asm volatile("bar.sync %0, %1;" ::"r"(id), "r"(n) : "memory"); }

__device__ __forceinline__ void tma2d(uint32_t dst, const CUtensorMap* m, int c0, int c1, uint32_t bar) {
  asm volatile("cp.async.bulk.tensor.2d.shared::cluster.global.mbarrier::complete_tx::bytes [%0], [%1, {%3, %4}], [%2];"
               ::"r"(dst), "l"(m), "r"(bar), "r"(c0), "r"(c1) : "memory");
}
__device__ __forceinline__ void tma2d_mc(uint32_t dst, const CUtensorMap* m, int c0, int c1, uint32_t bar, uint16_t mask) {
  asm volatile("cp.async.bulk.tensor.2d.shared::cluster.global.mbarrier::complete_tx::bytes.multicast::cluster [%0], [%1, {%3, %4}], [%2], %5;"
               ::"r"(dst), "l"(m), "r"(bar), "r"(c0), "r"(c1), "h"(mask) : "memory");
}
__device__ __forceinline__ void tma3d(uint32_t dst, const CUtensorMap* m, int c0, int c1, int c2, uint32_t bar) {
  asm volatile("cp.async.bulk.tensor.3d.shared::cluster.global.mbarrier::complete_tx::bytes [%0], [%1, {%3, %4, %5}], [%2];"
               ::"r"(dst), "l"(m), "r"(bar), "r"(c0), "r"(c1), "r"(c2) : "memory");
}
__device__ __forceinline__ void bulk_pf(const void* p, uint32_t bytes) {
  asm volatile("cp.async.bulk.prefetch.L2.global [%0], %1;" ::"l"(p), "r"(bytes) : "memory");
}
__device__ __forceinline__ void tma_st3d(const CUtensorMap* m, int c0, int c1, int c2, uint32_t src) {
  asm volatile("cp.async.bulk.tensor.3d.global.shared::cta.bulk_group [%0, {%1, %2, %3}], [%4];" ::"l"(m), "r"(c0), "r"(c1), "r"(c2), "r"(src) : "memory");
}
__device__ __forceinline__ void bulk_ld(uint32_t dst, const void* src, uint32_t bytes, uint32_t bar) {
  asm volatile("cp.async.bulk.shared::cluster.global.mbarrier::complete_tx::bytes [%0], [%1], %2, [%3];" ::"r"(dst), "l"(src), "r"(bytes), "r"(bar) : "memory");
}
__device__ __forceinline__ void bulk_st(void* dst, uint32_t src, uint32_t bytes) {
  asm volatile("cp.async.bulk.global.shared::cta.bulk_group [%0], [%1], %2;" ::"l"(dst), "r"(src), "r"(bytes) : "memory");
}
__device__ __forceinline__ void bulk_commit() { asm volatile("cp.async.bulk.commit_group;" ::: "memory"); }
__device__ __forceinline__ void bulk_wait_read0() { asm volatile("cp.async.bulk.wait_group.read 0;" ::: "memory"); }
__device__ __forceinline__ void bulk_wait0() { asm volatile("cp.async.bulk.wait_group 0;" ::: "memory"); }

__device__ __forceinline__ void wgmma_fence() { asm volatile("wgmma.fence.sync.aligned;" ::: "memory"); }
__device__ __forceinline__ void wgmma_commit() { asm volatile("wgmma.commit_group.sync.aligned;" ::: "memory"); }
template <int N> __device__ __forceinline__ void wgmma_wait() { asm volatile("wgmma.wait_group.sync.aligned %0;" ::"n"(N) : "memory"); }
template <int N> __device__ __forceinline__ void fence_regs(float* a) {
#pragma unroll
  for (int i = 0; i < N; i++) asm volatile("" : "+f"(a[i])::"memory");
}
template <int N> __device__ __forceinline__ void fence_regs_u(uint32_t* a) {
#pragma unroll
  for (int i = 0; i < N; i++) asm volatile("" : "+r"(a[i])::"memory");
}
__device__ __forceinline__ uint64_t make_desc(uint32_t addr, uint32_t lbo, uint32_t sbo, uint32_t swz) {
  return (uint64_t)((addr & 0x3FFFF) >> 4) | ((uint64_t)(lbo >> 4) << 16) | ((uint64_t)(sbo >> 4) << 32) | ((uint64_t)swz << 62);
}
__device__ __forceinline__ void ldsm4(uint32_t* r, uint32_t a) {
  asm volatile("ldmatrix.sync.aligned.m8n8.x4.shared.b16 {%0,%1,%2,%3}, [%4];" : "=r"(r[0]), "=r"(r[1]), "=r"(r[2]), "=r"(r[3]) : "r"(a) : "memory");
}
__device__ __forceinline__ void ldsm4t(uint32_t* r, uint32_t a) {
  asm volatile("ldmatrix.sync.aligned.m8n8.x4.trans.shared.b16 {%0,%1,%2,%3}, [%4];" : "=r"(r[0]), "=r"(r[1]), "=r"(r[2]), "=r"(r[3]) : "r"(a) : "memory");
}
__device__ __forceinline__ void stsm4(uint32_t a, uint32_t r0, uint32_t r1, uint32_t r2, uint32_t r3) {
  asm volatile("stmatrix.sync.aligned.m8n8.x4.shared.b16 [%0], {%1,%2,%3,%4};" ::"r"(a), "r"(r0), "r"(r1), "r"(r2), "r"(r3) : "memory");
}
__device__ __forceinline__ void stsm4t(uint32_t a, uint32_t r0, uint32_t r1, uint32_t r2, uint32_t r3) {
  asm volatile("stmatrix.sync.aligned.m8n8.x4.trans.shared.b16 [%0], {%1,%2,%3,%4};" ::"r"(a), "r"(r0), "r"(r1), "r"(r2), "r"(r3) : "memory");
}
__device__ __forceinline__ uint32_t lds32(uint32_t a) { uint32_t v; asm volatile("ld.shared.b32 %0, [%1];" : "=r"(v) : "r"(a) : "memory"); return v; }
__device__ __forceinline__ uint2 lds64(uint32_t a) { uint2 v; asm volatile("ld.shared.v2.b32 {%0,%1}, [%2];" : "=r"(v.x), "=r"(v.y) : "r"(a) : "memory"); return v; }
__device__ __forceinline__ uint4 lds128(uint32_t a) { uint4 v; asm volatile("ld.shared.v4.b32 {%0,%1,%2,%3}, [%4];" : "=r"(v.x), "=r"(v.y), "=r"(v.z), "=r"(v.w) : "r"(a) : "memory"); return v; }
__device__ __forceinline__ void sts16(uint32_t a, uint32_t v) { asm volatile("st.shared.u16 [%0], %1;" ::"r"(a), "h"((uint16_t)v) : "memory"); }
__device__ __forceinline__ void sts32(uint32_t a, uint32_t v) { asm volatile("st.shared.b32 [%0], %1;" ::"r"(a), "r"(v) : "memory"); }
__device__ __forceinline__ void sts64(uint32_t a, uint32_t x, uint32_t y) { asm volatile("st.shared.v2.b32 [%0], {%1,%2};" ::"r"(a), "r"(x), "r"(y) : "memory"); }
__device__ __forceinline__ void sts128(uint32_t a, uint32_t x, uint32_t y, uint32_t z, uint32_t w) { asm volatile("st.shared.v4.b32 [%0], {%1,%2,%3,%4};" ::"r"(a), "r"(x), "r"(y), "r"(z), "r"(w) : "memory"); }
__device__ __forceinline__ uint32_t pack_bf16(float lo, float hi) { uint32_t r; asm("cvt.rn.bf16x2.f32 %0, %1, %2;" : "=r"(r) : "f"(hi), "f"(lo)); return r; }
__device__ __forceinline__ float bf_lo(uint32_t v) { return __uint_as_float(v << 16); }
__device__ __forceinline__ float bf_hi(uint32_t v) { return __uint_as_float(v & 0xFFFF0000u); }
__device__ __forceinline__ float bf_round(float x) { return bf_lo(pack_bf16(x, 0.f)); }
__device__ __forceinline__ float ex2f(float x) { float r; asm("ex2.approx.ftz.f32 %0, %1;" : "=f"(r) : "f"(x)); return r; }
__device__ __forceinline__ float sinaf(float x) { float r; asm("sin.approx.ftz.f32 %0, %1;" : "=f"(r) : "f"(x)); return r; }
__device__ __forceinline__ float cosaf(float x) { float r; asm("cos.approx.ftz.f32 %0, %1;" : "=f"(r) : "f"(x)); return r; }
__device__ __forceinline__ float tanhaf(float x) { float r; asm("tanh.approx.f32 %0, %1;" : "=f"(r) : "f"(x)); return r; }
__device__ __forceinline__ uint32_t hsub2_bf(uint32_t a, uint32_t b) { uint32_t r; asm("sub.rn.bf16x2 %0, %1, %2;" : "=r"(r) : "r"(a), "r"(b)); return r; }
__device__ __forceinline__ uint32_t hadd2_bf(uint32_t a, uint32_t b) { uint32_t r; asm("add.rn.bf16x2 %0, %1, %2;" : "=r"(r) : "r"(a), "r"(b)); return r; }
__device__ __forceinline__ uint32_t hmul2_bf(uint32_t a, uint32_t b) { uint32_t r; asm("mul.rn.bf16x2 %0, %1, %2;" : "=r"(r) : "r"(a), "r"(b)); return r; }
__device__ __forceinline__ void mma16816(float* c, uint32_t a0, uint32_t a1, uint32_t a2, uint32_t a3, uint32_t b0, uint32_t b1) {
  asm volatile("mma.sync.aligned.m16n8k16.row.col.f32.bf16.bf16.f32 {%0,%1,%2,%3},{%4,%5,%6,%7},{%8,%9},{%0,%1,%2,%3};"
               : "+f"(c[0]), "+f"(c[1]), "+f"(c[2]), "+f"(c[3]) : "r"(a0), "r"(a1), "r"(a2), "r"(a3), "r"(b0), "r"(b1));
}

template<int TA, int TB> __device__ __forceinline__ void wgmma_n176_ss(float* d, uint64_t da, uint64_t db, int scale_d) {
  asm volatile("{\n.reg .pred p;\n"
    "setp.ne.b32 p, %90, 0;\n"
    "wgmma.mma_async.sync.aligned.m64n176k16.f32.bf16.bf16 {%0, %1, %2, %3, %4, %5, %6, %7, %8, %9, %10, %11, %12, %13, %14, %15, %16, %17, %18, %19, %20, %21, %22, %23, %24, %25, %26, %27, %28, %29, %30, %31, %32, %33, %34, %35, %36, %37, %38, %39, %40, %41, %42, %43, %44, %45, %46, %47, %48, %49, %50, %51, %52, %53, %54, %55, %56, %57, %58, %59, %60, %61, %62, %63, %64, %65, %66, %67, %68, %69, %70, %71, %72, %73, %74, %75, %76, %77, %78, %79, %80, %81, %82, %83, %84, %85, %86, %87}, %88, %89, p, 1, 1, %91, %92;\n}\n"
    : "+f"(d[0]), "+f"(d[1]), "+f"(d[2]), "+f"(d[3]), "+f"(d[4]), "+f"(d[5]), "+f"(d[6]), "+f"(d[7]), "+f"(d[8]), "+f"(d[9]), "+f"(d[10]), "+f"(d[11]), "+f"(d[12]), "+f"(d[13]), "+f"(d[14]), "+f"(d[15]), "+f"(d[16]), "+f"(d[17]), "+f"(d[18]), "+f"(d[19]), "+f"(d[20]), "+f"(d[21]), "+f"(d[22]), "+f"(d[23]), "+f"(d[24]), "+f"(d[25]), "+f"(d[26]), "+f"(d[27]), "+f"(d[28]), "+f"(d[29]), "+f"(d[30]), "+f"(d[31]), "+f"(d[32]), "+f"(d[33]), "+f"(d[34]), "+f"(d[35]), "+f"(d[36]), "+f"(d[37]), "+f"(d[38]), "+f"(d[39]), "+f"(d[40]), "+f"(d[41]), "+f"(d[42]), "+f"(d[43]), "+f"(d[44]), "+f"(d[45]), "+f"(d[46]), "+f"(d[47]), "+f"(d[48]), "+f"(d[49]), "+f"(d[50]), "+f"(d[51]), "+f"(d[52]), "+f"(d[53]), "+f"(d[54]), "+f"(d[55]), "+f"(d[56]), "+f"(d[57]), "+f"(d[58]), "+f"(d[59]), "+f"(d[60]), "+f"(d[61]), "+f"(d[62]), "+f"(d[63]), "+f"(d[64]), "+f"(d[65]), "+f"(d[66]), "+f"(d[67]), "+f"(d[68]), "+f"(d[69]), "+f"(d[70]), "+f"(d[71]), "+f"(d[72]), "+f"(d[73]), "+f"(d[74]), "+f"(d[75]), "+f"(d[76]), "+f"(d[77]), "+f"(d[78]), "+f"(d[79]), "+f"(d[80]), "+f"(d[81]), "+f"(d[82]), "+f"(d[83]), "+f"(d[84]), "+f"(d[85]), "+f"(d[86]), "+f"(d[87])
    : "l"(da), "l"(db), "r"(scale_d), "n"(TA), "n"(TB));
}
template<int TA, int TB> __device__ __forceinline__ void wgmma_n128_ss(float* d, uint64_t da, uint64_t db, int scale_d) {
  asm volatile("{\n.reg .pred p;\n"
    "setp.ne.b32 p, %66, 0;\n"
    "wgmma.mma_async.sync.aligned.m64n128k16.f32.bf16.bf16 {%0, %1, %2, %3, %4, %5, %6, %7, %8, %9, %10, %11, %12, %13, %14, %15, %16, %17, %18, %19, %20, %21, %22, %23, %24, %25, %26, %27, %28, %29, %30, %31, %32, %33, %34, %35, %36, %37, %38, %39, %40, %41, %42, %43, %44, %45, %46, %47, %48, %49, %50, %51, %52, %53, %54, %55, %56, %57, %58, %59, %60, %61, %62, %63}, %64, %65, p, 1, 1, %67, %68;\n}\n"
    : "+f"(d[0]), "+f"(d[1]), "+f"(d[2]), "+f"(d[3]), "+f"(d[4]), "+f"(d[5]), "+f"(d[6]), "+f"(d[7]), "+f"(d[8]), "+f"(d[9]), "+f"(d[10]), "+f"(d[11]), "+f"(d[12]), "+f"(d[13]), "+f"(d[14]), "+f"(d[15]), "+f"(d[16]), "+f"(d[17]), "+f"(d[18]), "+f"(d[19]), "+f"(d[20]), "+f"(d[21]), "+f"(d[22]), "+f"(d[23]), "+f"(d[24]), "+f"(d[25]), "+f"(d[26]), "+f"(d[27]), "+f"(d[28]), "+f"(d[29]), "+f"(d[30]), "+f"(d[31]), "+f"(d[32]), "+f"(d[33]), "+f"(d[34]), "+f"(d[35]), "+f"(d[36]), "+f"(d[37]), "+f"(d[38]), "+f"(d[39]), "+f"(d[40]), "+f"(d[41]), "+f"(d[42]), "+f"(d[43]), "+f"(d[44]), "+f"(d[45]), "+f"(d[46]), "+f"(d[47]), "+f"(d[48]), "+f"(d[49]), "+f"(d[50]), "+f"(d[51]), "+f"(d[52]), "+f"(d[53]), "+f"(d[54]), "+f"(d[55]), "+f"(d[56]), "+f"(d[57]), "+f"(d[58]), "+f"(d[59]), "+f"(d[60]), "+f"(d[61]), "+f"(d[62]), "+f"(d[63])
    : "l"(da), "l"(db), "r"(scale_d), "n"(TA), "n"(TB));
}
template<int TA, int TB> __device__ __forceinline__ void wgmma_n64_ss(float* d, uint64_t da, uint64_t db, int scale_d) {
  asm volatile("{\n.reg .pred p;\n"
    "setp.ne.b32 p, %34, 0;\n"
    "wgmma.mma_async.sync.aligned.m64n64k16.f32.bf16.bf16 {%0, %1, %2, %3, %4, %5, %6, %7, %8, %9, %10, %11, %12, %13, %14, %15, %16, %17, %18, %19, %20, %21, %22, %23, %24, %25, %26, %27, %28, %29, %30, %31}, %32, %33, p, 1, 1, %35, %36;\n}\n"
    : "+f"(d[0]), "+f"(d[1]), "+f"(d[2]), "+f"(d[3]), "+f"(d[4]), "+f"(d[5]), "+f"(d[6]), "+f"(d[7]), "+f"(d[8]), "+f"(d[9]), "+f"(d[10]), "+f"(d[11]), "+f"(d[12]), "+f"(d[13]), "+f"(d[14]), "+f"(d[15]), "+f"(d[16]), "+f"(d[17]), "+f"(d[18]), "+f"(d[19]), "+f"(d[20]), "+f"(d[21]), "+f"(d[22]), "+f"(d[23]), "+f"(d[24]), "+f"(d[25]), "+f"(d[26]), "+f"(d[27]), "+f"(d[28]), "+f"(d[29]), "+f"(d[30]), "+f"(d[31])
    : "l"(da), "l"(db), "r"(scale_d), "n"(TA), "n"(TB));
}

struct Params {
  const __nv_bfloat16 *Are, *Aim, *Bre, *Bim, *Cre, *Cim, *logdt, *x, *dskip, *wg, *wu, *wd;
  __nv_bfloat16* out;
  int nhelp;
};

__device__ __forceinline__ void expand8(uint32_t src, uint32_t dst, bool flip) {
  const uint4 lo = lds128(src), hi = lds128(src + 16);
  const uint32_t s0 = __byte_perm(lo.x, lo.y, 0x5432), s1 = __byte_perm(lo.y, lo.z, 0x5432), s2 = __byte_perm(lo.z, lo.w, 0x5432),
                 s3 = __byte_perm(lo.w, hi.x, 0x5432), s4 = __byte_perm(hi.x, hi.y, 0x5432), s5 = __byte_perm(hi.y, hi.z, 0x5432),
                 s6 = __byte_perm(hi.z, hi.w, 0x5432);
  const uint32_t d0 = flip ? dst : dst + 112;
  const int st = flip ? 16 : -16;
  sts128(d0, lo.x, lo.y, lo.z, lo.w);
  sts128(d0 + st, s0, s1, s2, s3);
  sts128(d0 + 2 * st, lo.y, lo.z, lo.w, hi.x);
  sts128(d0 + 3 * st, s1, s2, s3, s4);
  sts128(d0 + 4 * st, lo.z, lo.w, hi.x, hi.y);
  sts128(d0 + 5 * st, s2, s3, s4, s5);
  sts128(d0 + 6 * st, lo.w, hi.x, hi.y, hi.z);
  sts128(d0 + 7 * st, s3, s4, s5, s6);
}
__device__ __forceinline__ void build_tap_task(int j, uint32_t rb, uint32_t cb) {
  const bool far = j >= 148;
  const int i = j - 148, f = i >> 3;
  expand8(far ? rb + 2432 + f * 160 + (i & 7) * 16 : rb + (j & 3) * 608 + (j >> 2) * 16,
          cb + (far ? CB_B3 + f * 2448 + (i & 7) * 144 : CB_H + j * 144), far);
}
__device__ __forceinline__ void build_z(uint32_t cb, int w, int lane) {
  const int bg = w & 1, sg = 32 * (w >> 1) + lane, ci = 2 * sg + bg;
  auto ua = [&](int k) { return cb + CB_U + (k & 1) * U_JS + (127 - (k >> 1)) * 16; };
  const uint2 u0 = lds64(ua(ci - 2) + 8);
  const uint4 u1 = lds128(ua(ci - 1));
  const uint2 u2 = lds64(ua(ci));
  float wv[16];
  wv[0] = bf_lo(u0.x); wv[1] = bf_hi(u0.x); wv[2] = bf_lo(u0.y); wv[3] = bf_hi(u0.y);
  wv[4] = bf_lo(u1.x); wv[5] = bf_hi(u1.x); wv[6] = bf_lo(u1.y); wv[7] = bf_hi(u1.y);
  wv[8] = bf_lo(u1.z); wv[9] = bf_hi(u1.z); wv[10] = bf_lo(u1.w); wv[11] = bf_hi(u1.w);
  wv[12] = bf_lo(u2.x); wv[13] = bf_hi(u2.x); wv[14] = bf_lo(u2.y); wv[15] = bf_hi(u2.y);
  float v7[8];
  const float core = (wv[4] + wv[5]) + (wv[6] + wv[7]);
  v7[0] = core + ((wv[1] + wv[2]) + wv[3]);
  v7[1] = core + ((wv[2] + wv[3]) + wv[8]);
  v7[2] = core + ((wv[3] + wv[8]) + wv[9]);
  v7[3] = core + ((wv[8] + wv[9]) + wv[10]);
  const float core2 = (wv[8] + wv[9]) + (wv[10] + wv[11]);
  v7[4] = core2 + ((wv[5] + wv[6]) + wv[7]);
  v7[5] = core2 + ((wv[6] + wv[7]) + wv[12]);
  v7[6] = core2 + ((wv[7] + wv[12]) + wv[13]);
  v7[7] = core2 + ((wv[12] + wv[13]) + wv[14]);
  uint32_t p9[4];
#pragma unroll
  for (int e = 0; e < 4; e++) p9[e] = pack_bf16(v7[2 * e] + (wv[2 * e] + wv[8 + 2 * e]), v7[2 * e + 1] + (wv[2 * e + 1] + wv[9 + 2 * e]));
  sts128(cb + CB_Z + (1 - bg) * 1024 + sg * 16, pack_bf16(v7[0], v7[1]), pack_bf16(v7[2], v7[3]), pack_bf16(v7[4], v7[5]), pack_bf16(v7[6], v7[7]));
  const bool z = ci == 127;
  sts128(cb + CB_Z + 2048 + bg * 1024 + ((sg + bg) & 63) * 16, z ? 0 : p9[0], z ? 0 : p9[1], z ? 0 : p9[2], z ? 0 : p9[3]);
}
struct cpx { float r, i; };
__device__ __forceinline__ cpx cmul(cpx a, cpx b) { cpx o; o.r = fmaf(a.r, b.r, -a.i * b.i); o.i = fmaf(a.r, b.i, a.i * b.r); return o; }
__device__ __forceinline__ cpx zpow(float a2, float om, float t) { const float m = ex2f(t * a2); cpx o; o.r = m * cosaf(t * om); o.i = m * sinaf(t * om); return o; }

struct StateP { uint32_t are, aim, bre, bim, cre, cim, ldt; };
__device__ __forceinline__ StateP load_state(const Params& P, int bid, int task, int lane) {
  typedef const unsigned short* usp;
  const int chan = bid * 4 + (task >> 2);
  const size_t po = (size_t)chan * NST + (task & 3) * 32 + lane;
  StateP p;
  p.ldt = __ldg((usp)P.logdt + chan);
  p.are = __ldg((usp)P.Are + po); p.aim = __ldg((usp)P.Aim + po); p.bre = __ldg((usp)P.Bre + po);
  p.bim = __ldg((usp)P.Bim + po); p.cre = __ldg((usp)P.Cre + po); p.cim = __ldg((usp)P.Cim + po);
  return p;
}
template <class F>
__device__ __forceinline__ void kgen_task(const StateP& p, uint32_t tab, int lane, F mid) {
    const float dt = bf_round(ex2f(bf_lo(p.ldt) * 1.4426950408889634f));
    const float a2 = (dt * bf_lo(p.are)) * 1.4426950408889634f, om = dt * bf_lo(p.aim);
    uint32_t bfr[2][3][4];
    {
      const float br = dt * bf_lo(p.bre), bi = dt * bf_lo(p.bim), cr = bf_lo(p.cre), ci = bf_lo(p.cim);
      cpx z1 = zpow(a2, om, 1.f), z256 = zpow(a2, om, 256.f);
      z1.i = -z1.i; z256.i = -z256.i;
      const cpx z2 = cmul(z1, z1);
      cpx e[4], o[4];
      e[0].r = fmaf(cr, br, -ci * bi); e[0].i = -fmaf(cr, bi, ci * br);
      o[0] = cmul(e[0], z1);
#pragma unroll
      for (int k = 1; k < 4; k++) { e[k] = cmul(e[k - 1], z2); o[k] = cmul(o[k - 1], z2); }
      const uint32_t ta = tab + lane * 112;
      sts128(ta, pack_bf16(e[0].r, o[0].r), pack_bf16(e[1].r, o[1].r), pack_bf16(e[2].r, o[2].r), pack_bf16(e[3].r, o[3].r));
      sts128(ta + 48, pack_bf16(e[0].i, o[0].i), pack_bf16(e[1].i, o[1].i), pack_bf16(e[2].i, o[2].i), pack_bf16(e[3].i, o[3].i));
#pragma unroll
      for (int k = 0; k < 4; k++) e[k] = cmul(e[k], z256);
      o[0] = cmul(e[0], z256); o[1] = cmul(e[2], z256); o[2] = cmul(o[0], z256); o[3] = cmul(o[1], z256);
      sts128(ta + 16, pack_bf16(e[0].r, e[1].r), pack_bf16(e[2].r, e[3].r), pack_bf16(o[0].r, o[1].r), pack_bf16(o[2].r, o[3].r));
      sts128(ta + 64, pack_bf16(e[0].i, e[1].i), pack_bf16(e[2].i, e[3].i), pack_bf16(o[0].i, o[1].i), pack_bf16(o[2].i, o[3].i));
      const cpx z512 = cmul(z256, z256);
      e[0] = cmul(o[0], z512); e[1] = cmul(o[2], z512); e[2] = cmul(e[0], z512); e[3] = cmul(e[1], z512); o[0] = cmul(e[2], z512);
      sts128(ta + 32, pack_bf16(e[0].r, e[1].r), pack_bf16(e[2].r, e[3].r), pack_bf16(o[0].r, 0.f), 0);
      sts128(ta + 80, pack_bf16(e[0].i, e[1].i), pack_bf16(e[2].i, e[3].i), pack_bf16(o[0].i, 0.f), 0);
      __syncwarp();
      const uint32_t ba = tab + (8 * (lane >> 4) + (lane & 7)) * 112 + ((lane >> 3) & 1) * 48;
#pragma unroll
      for (int k2 = 0; k2 < 2; k2++)
#pragma unroll
        for (int j = 0; j < 3; j++) ldsm4t(bfr[k2][j], ba + k2 * 16 * 112 + j * 16);
      __syncwarp();
    }
    {
      cpx y[4];
      y[0].r = 1.f; y[0].i = 0.f;
      mid();
      float a2v = a2, omv = om;
      asm volatile("" : "+f"(a2v), "+f"(omv));
      y[1] = zpow(a2v, omv, 8.f);
      const cpx p32 = zpow(a2v, omv, 32.f);
      y[2] = cmul(y[1], y[1]);
      y[3] = cmul(y[2], y[1]);
      const uint32_t ta = tab + lane * 144;
#pragma unroll
      for (int j = 0; j < 4; j++) {
        if (j > 0) {
#pragma unroll
          for (int r = 0; r < 4; r++) y[r] = cmul(y[r], p32);
        }
        const uint32_t r0 = pack_bf16(y[0].r, y[1].r), r1 = pack_bf16(y[2].r, y[3].r), i0 = pack_bf16(y[0].i, y[1].i), i1 = pack_bf16(y[2].i, y[3].i);
        if (j == 0) y[0] = p32; else y[0] = cmul(y[0], p32);
#pragma unroll
        for (int r = 1; r < 4; r++) y[r] = cmul(y[r], p32);
        sts128(ta + j * 16, r0, r1, pack_bf16(y[0].r, y[1].r), pack_bf16(y[2].r, y[3].r));
        sts128(ta + 64 + j * 16, i0, i1, pack_bf16(y[0].i, y[1].i), pack_bf16(y[2].i, y[3].i));
      }
    }
    __syncwarp();
    float ka[2][3][4];
#pragma unroll
    for (int i = 0; i < 2; i++)
#pragma unroll
      for (int j = 0; j < 3; j++)
#pragma unroll
        for (int k = 0; k < 4; k++) ka[i][j][k] = 0.f;
    const uint32_t aa = tab + (lane & 7) * 144 + (lane >> 4) * 64 + ((lane >> 3) & 1) * 16;
#pragma unroll
    for (int ks = 0; ks < 4; ks++)
#pragma unroll
      for (int i = 0; i < 2; i++) {
        uint32_t af[4];
        ldsm4t(af, aa + ks * 8 * 144 + i * 32);
#pragma unroll
        for (int j = 0; j < 3; j++) mma16816(ka[i][j], af[0], af[1], af[2], af[3], bfr[ks >> 1][j][2 * (ks & 1)], bfr[ks >> 1][j][2 * (ks & 1) + 1]);
      }
    __syncwarp();
#pragma unroll
    for (int i = 0; i < 2; i++)
#pragma unroll
      for (int j = 0; j < 3; j++)
        sts128(tab + (i * 3 + j) * 512 + lane * 16, __float_as_uint(ka[i][j][0]), __float_as_uint(ka[i][j][1]), __float_as_uint(ka[i][j][2]), __float_as_uint(ka[i][j][3]));
    __syncwarp();
}

constexpr int CSN = (DM - KSPLIT + 9) / 10;
__device__ __forceinline__ void colsum_cta(const Params& P, int e, float* sm) {
  const int tid = threadIdx.x, rg = tid / 86, ch = tid - 86 * rg;
  float s[8];
#pragma unroll
  for (int i = 0; i < 8; i++) s[i] = 0.f;
  if (tid == 511) {
    unsigned ticket;
    asm volatile("atom.relaxed.gpu.global.add.u32 %0, [%1], 1;" : "=r"(ticket) : "l"(&g_cnt[CNT_TICKET * 32]) : "memory");
    sm[4096] = __uint_as_float(ticket / 132u + 1u);
  }
  if (rg < 5) {
    const uint4* src = reinterpret_cast<const uint4*>(((e >> 1) ? P.wu : P.wg) + (size_t)(KSPLIT + rg) * FF + (e & 1) * 688) + ch;
#pragma unroll 1
    for (int r = KSPLIT + rg; r < DM; r += 5 * CSN) {
      uint4 v[CSN];
#pragma unroll
      for (int k = 0; k < CSN; k++) v[k] = r + 5 * k < DM ? __ldg(src + k * (5 * FF / 8)) : make_uint4(0, 0, 0, 0);
      src += 5 * CSN * FF / 8;
#pragma unroll
      for (int k = 0; k < CSN; k++) {
        s[0] += bf_lo(v[k].x); s[1] += bf_hi(v[k].x); s[2] += bf_lo(v[k].y); s[3] += bf_hi(v[k].y);
        s[4] += bf_lo(v[k].z); s[5] += bf_hi(v[k].z); s[6] += bf_lo(v[k].w); s[7] += bf_hi(v[k].w);
      }
    }
#pragma unroll
    for (int i = 0; i < 8; i++) sm[rg * 688 + ch * 8 + i] = s[i];
  }
  __syncthreads();
  const unsigned ep1 = __float_as_uint(sm[4096]);
  for (int c = tid; c < 688; c += 512)
    st_tag(&g_cs[1][(e >> 1) * FP + (e & 1) * 688 + c], __float_as_uint(((sm[c] + sm[688 + c]) + (sm[1376 + c] + sm[2064 + c])) + sm[2752 + c]), ep1);
}

constexpr uint32_t SB0 = 1024;
#define SB_EXPR (SB0 | ((uint32_t)(blockIdx.x & 1) << 24))
#define ROLE_IDS()                                                                                   \
  int tid;                                                                                           \
  asm volatile("mov.u32 %0, %%tid.x;" : "=r"(tid));                                                  \
  const int bid = (int)blockIdx.x;                                                            \
  const uint32_t sb = SB_EXPR;                                                                       \
  const int warp = tid >> 5, lane = tid & 31, pair = bid >> 1;                                       \
  const uint32_t rank = bid & 1, bars = sb + OFF_BAR;                                                \
  const int mt1 = (pair & 7) * 2 + rank, nt = pair >> 3, mt2 = pair >> 2, dp = pair & 3;             \
  (void)warp; (void)lane; (void)rank; (void)bars; (void)mt1; (void)nt; (void)mt2; (void)dp

#define REG_CONS 208
#define REG_AUX 64
#define REG_PROD 32
constexpr int G2_S1 = 1, G2_S2 = 3;
constexpr int EARLY_W = 2;
constexpr int TAB_LATE = 15;
#define STR2(x) #x
#define STR(x) STR2(x)

__global__ void __cluster_dims__(2, 1, 1) __launch_bounds__(512, 1)
fused_kernel(const Params P, const __grid_constant__ CUtensorMap mX, const __grid_constant__ CUtensorMap mWg, const __grid_constant__ CUtensorMap mWu,
             const __grid_constant__ CUtensorMap mHst, const __grid_constant__ CUtensorMap mHld, const __grid_constant__ CUtensorMap mWd,
             const __grid_constant__ CUtensorMap mS, const __grid_constant__ CUtensorMap mWg48, const __grid_constant__ CUtensorMap mWu48,
             const __grid_constant__ CUtensorMap mH32, const __grid_constant__ CUtensorMap mWd32) {
  extern __shared__ __align__(1024) uint8_t smem_raw[];
#define BAR(i) (bars + 8u * (i))
#define CLUSTER_ARRIVE() asm volatile("barrier.cluster.arrive.relaxed.aligned;" ::: "memory")
#define CLUSTER_WAIT() asm volatile("barrier.cluster.wait.acquire.aligned;" ::: "memory")
  if (blockIdx.x >= 128) {
    colsum_cta(P, blockIdx.x & 3, reinterpret_cast<float*>(smem_raw));
    return;
  }
  if ((uint32_t)__cvta_generic_to_shared(smem_raw) != SB_EXPR) return;
  const int role = threadIdx.x >> 7;
  {
    ROLE_IDS();
    const StateP sp = load_state(P, bid, warp, lane);
    unsigned ticket = 0;
    if (tid == 160) asm volatile("atom.relaxed.gpu.global.add.u32 %0, [%1], 1;" : "=r"(ticket) : "l"(&g_cnt[CNT_TICKET * 32]) : "memory");
    const CUtensorMap* mW = rank ? &mWu : &mWg;
    if (__builtin_expect(tid == 0, 0)) {
#pragma unroll
      for (int b = 0; b < B_COUNT; b++) mbar_init(BAR(b), bar_count(b));
      asm volatile("fence.mbarrier_init.release.cluster;" ::: "memory");
      TSTAMP(48);
    }
    if (lane == 0 && warp >= 5) asm volatile("prefetch.tensormap [%0];" ::"l"(&mX + (warp - 5)) : "memory");
    __syncwarp();
    CLUSTER_ARRIVE();
    auto pf = [](const void* p) { asm volatile("prefetch.global.L2 [%0];" ::"l"(p)); };
    auto wline = [&](int row, int t) { return ((t & 4) ? P.wu : P.wg) + (size_t)row * FF + min(nt * 176 + (t & 3) * 56, FF - 8); };
    {
      const int t = tid - 256;
      const __nv_bfloat16* p = t < 64 ? wline((t >> 3) * 16 + mt1, t) : P.x + (size_t)(mt1 * 128 + nt * 16 + (t & 15)) * DM + ((t >> 4) - 4) * 64;
      if (t >= 0 && t < 112) pf(p);
    }
    auto first_loads = [&]() {
      CLUSTER_WAIT();
      if (lane == 0) {
        if (warp == 0) TSTAMP(0);
        if (warp != 1) {
          const int kb = (warp + 1) >> 1;
          mbar_expect_tx(BAR(B_FULLA + kb), SLOT);
          tma2d(sb + OFF_A + kb * SLOT, &mX, kb * 64, mt1 * 128, BAR(B_FULLA + kb));
        }
        const uint32_t f = BAR(B_FULLB + warp);
        mbar_expect_tx(f, BTX);
#pragma unroll
        for (int a = 0; a < 3; a++) tma2d_mc(sb + OFF_B + warp * BST + rank * 12288 + a * 4096, a < 2 ? mW : mW + 6, nt * 176 + a * 64, warp * 32, f, 3);
        if (warp == 0) TSTAMP(1);
      }
      __syncwarp();
    };
    if (__builtin_expect(warp < EARLY_W, 0)) first_loads();
    kgen_task(sp, sb + OFF_CB + warp * KG_TAB, lane, [&]() {
      if (__builtin_expect(role == 0 && warp >= EARLY_W, 0)) first_loads();
      const int t = tid - 128, u = tid - 256;
      const __nv_bfloat16* p = u < 0 ? P.x + (size_t)(32 * (bid >> 1) + 8 * (bid & 1) + (t >> 6) * 16 + ((t >> 3) & 7)) * DM + (t & 7) * 64
                                     : wline(128 + (u >> 3) * 16 + mt1, u);
      if (t >= 0 && u < 192) pf(p);
    });
    if (tid == 0) TSTAMP(41);
    if (role != 0) CLUSTER_WAIT();
    if (tid == 256) TSTAMP(59);
    if (lane == 0) mbar_arrive(BAR(B_KG));
    if (tid == 160) {
      sts32(sb + OFF_EPOCH, (P.nhelp ? ticket / 132u : ticket >> 7) + 1u);
      mbar_arrive(BAR(B_EPOCH));
    }
  }
  if (role == 0) {
    asm volatile("setmaxnreg.dec.sync.aligned.u32 " STR(REG_PROD) ";");
    ROLE_IDS();
    if (warp == 0) {
      if (lane == 0) {
        const CUtensorMap* mW = rank ? &mWu : &mWg;
        auto loadA = [&](int kb) {
          const uint32_t f = BAR(B_FULLA + kb % 3);
          mbar_expect_tx(f, SLOT);
          tma2d(sb + OFF_A + (kb % 3) * SLOT, &mX, kb * 64, mt1 * 128, f);
        };
        auto loadB = [&](int hb) {
          const uint32_t f = BAR(B_FULLB + (hb & 3));
          mbar_expect_tx(f, BTX);
          const uint32_t d = sb + OFF_B + (hb & 3) * BST + rank * 12288;
#pragma unroll
          for (int a = 0; a < 3; a++) tma2d_mc(d + a * 4096, a < 2 ? mW : mW + 6, nt * 176 + a * 64, hb * 32, f, 3);
        };
        const int k2 = 704 * rank;
        auto loadWd = [&](int i) {
          const uint32_t f = BAR(B_FULL2 + i);
          mbar_expect_tx(f, i < 9 ? SLOT : i < 12 ? 8192 : 4096);
          tma2d(sb + wd_slot(i), i < 12 ? &mWd : &mWd32, dp * 128 + 64 * rank, i < 9 ? k2 + 64 * i : i < 11 ? 64 * i : 704 + 64 * (i - 2), f);
          if (i < 9) tma2d(sb + wd_slot(i) + 8192, &mWd, dp * 128 + 64 * (rank ^ 1), k2 + 64 * i, f);
        };
        auto loadH = [&](int i) {
          const uint32_t f = BAR(B_FULL2 + i);
          mbar_expect_tx(f, SLOT);
          tma2d(sb + h_slot(i), &mHld, k2 + 64 * i, mt2 * 128, f);
        };
        mbar_expect_tx(BAR(B_XCF), 16384);
#pragma unroll 1
        for (int j = 0; j < 12; j++) {
          mbar_wait(BAR(B_EMPTYB + (j & 3)), (j >> 2) & 1);
          loadB(j + 4);
          if (j == 0) bulk_pf(P.wd + (size_t)bid * (FF * DM / 128), FF * DM * 2 / 128);
          if (j & 1) {
            const int kb = j >> 1;
            mbar_wait(BAR(B_EMPTYA + kb % 3), (kb / 3) & 1);
            if (kb < 5) loadA(kb + 3); else loadWd(0);
          }
        }
        mbar_wait(BAR(B_EMPTYB + 0), 1); loadWd(1);
        mbar_wait(BAR(B_EMPTYB + 1), 1); mbar_wait(BAR(B_EMPTYA + 0), 0);
        loadWd(2); loadWd(3); loadWd(4);
        mbar_wait(BAR(B_EMPTYB + 2), 1); loadWd(5);
        TSTAMP(2);
        mbar_wait(BAR(B_EPOCH), 0);
        poll_ge(&g_cnt[(CNT_H + mt2) * 32 + 16 * rank], lds32(sb + OFF_EPOCH) * 12u);
        TSTAMP(3);
        mbar_wait(BAR(B_STG), 0); loadH(0); loadH(1); loadH(2);
        TSTAMP(4);
        mbar_wait(BAR(B_CF + 2), 0); loadH(3); loadH(4);
        mbar_wait(BAR(B_REL2 + 0), 0); loadH(5); loadH(6);
        mbar_wait(BAR(B_REL2 + 1), 0); loadWd(6); loadH(7);
        mbar_wait(BAR(B_REL2 + 2), 0); loadWd(7); loadH(8);
#pragma unroll
        for (int i = 9; i < 13; i++) mbar_expect_tx(BAR(B_FULL2 + i), i < 12 ? SLOT : 8192);
        auto tail_h = [&]() {
          mbar_wait(BAR(rank ? B_CF3 : B_TF), 0);
#pragma unroll
          for (int j = 0; j < 2; j++)
            tma2d_mc(sb + (rank ? h_slot(11 + j) : h_slot(9 + j)), (j && rank) ? &mH32 : &mHld, k2 + 64 * (9 + j), mt2 * 128, BAR(B_FULL2 + 9 + j) + 16 * rank, 3);
        };
        mbar_wait(BAR(B_REL2 + 3), 0); loadWd(8);
        mbar_wait(BAR(B_REL2 + 4), 0); loadWd(9); loadWd(10);
        tail_h();
        mbar_wait(BAR(B_REL2 + 5), 0); loadWd(11); loadWd(12);
        mbar_wait(BAR(B_REL2 + 6), 0);
        mbar_expect_tx(BAR(B_XF), SLOT);
        tma2d(sb + OFF_XT, &mX, dp * 128 + 64 * rank, mt2 * 128, BAR(B_XF));
        TSTAMP(5);
      }
    } else {
      mbar_wait(BAR(B_EPOCH), 0);
      const unsigned ep1 = lds32(sb + OFF_EPOCH);
      {
        const uint32_t e_rem = mapa(BAR(B_EMPTYB), rank ^ 1);
        const int nsum = P.nhelp ? KSPLIT / 32 : 16;
        const int c = mt1 + 16 * (warp - 1);
        const int mat = c >= 22, cc = c - 22 * mat;
        const uint32_t off = sb + OFF_B + mat * 12288 + (cc >> 3) * 4096 + lane * 128 + (((cc & 7) ^ (lane & 7)) << 4);
        float s0 = 0.f, s1 = 0.f;
#pragma unroll 1
        for (int hb = 0; hb < nsum; hb++) {
          mbar_wait(BAR(B_FULLB + (hb & 3)), (hb >> 2) & 1);
          if (c < 44) {
            uint32_t v[4];
            ldsm4(v, off + (hb & 3) * BST);
            s0 += (bf_lo(v[0]) + bf_lo(v[1])) + (bf_lo(v[2]) + bf_lo(v[3]));
            s1 += (bf_hi(v[0]) + bf_hi(v[1])) + (bf_hi(v[2]) + bf_hi(v[3]));
          }
          __syncwarp();
          if (lane == 0) {
            mbar_arrive(BAR(B_EMPTYB + (hb & 3))); mbar_arrive_remote(e_rem + 8 * (hb & 3));
          }
          __syncwarp();
        }
        if (c < 44) {
          const bool up = lane & 16;
          s0 = (up ? s1 : s0) + __shfl_xor_sync(~0u, up ? s0 : s1, 16);
          s0 += __shfl_xor_sync(~0u, s0, 8);
          s0 += __shfl_xor_sync(~0u, s0, 4);
          if (!(lane & 12)) st_tag(&g_cs[0][mat * FP + nt * 176 + cc * 8 + 2 * (lane & 3) + (lane >> 4)], __float_as_uint(s0), ep1);
        }
      }
      if (warp == 1 && lane == 0) TSTAMP(7);
      {
        const int u = tid - 32;
        if (u < 64) {
          uint4 v;
          int tries = 0;
          for (;;) { v = ld_tag2(&g_stats[mt1 * 128 + 2 * u]); if ((((v.y ^ ep1) | (v.w ^ ep1)) & 0xFFFFu) == 0 || ++tries > 100000) break; __nanosleep(200); }
          const uint32_t n0 = (v.y >> 16) ^ 0x8000u, n1 = (v.w >> 16) ^ 0x8000u;
          sts128(sb + OFF_MA + u * 32, n0 * 0x10001u, n0, 0, 0);
          sts128(sb + OFF_MA + u * 32 + 16, n1 * 0x10001u, n1, 0, 0);
          sts64(sb + OFF_STAT + u * 8, __float_as_uint(0.5f * __uint_as_float(v.x)), __float_as_uint(0.5f * __uint_as_float(v.z)));
        } else if (u < 70) sts128(sb + OFF_CS + 2112 + (u - 64) * 16, 0, 0, 0, 0);
        const int lim2 = P.nhelp ? (nt == 7 ? 72 : 88) : 0;
#pragma unroll 1
        for (int e = u; e < 176; e += 96) {
          const int m = e >= 88, p = e - 88 * m;
          const uint2* src = &g_cs[0][m * FP + nt * 176 + 2 * p];
          uint4 a, b;
          int tries = 0;
          bool ok;
          do {
            a = ld_tag2(src);
            b = make_uint4(0, ep1, 0, ep1);
            if (p < lim2) b = ld_tag2(src + 2 * FP);
            ok = a.y == ep1 && a.w == ep1 && b.y == ep1 && b.w == ep1;
            if (!ok) __nanosleep(100);
          } while (!ok && ++tries < 100000);
          float v0 = 0.5f * (__uint_as_float(a.x) + __uint_as_float(b.x)), v1 = 0.5f * (__uint_as_float(a.z) + __uint_as_float(b.z));
          const uint32_t ca = sb + OFF_CS + (e >> 2) * 48 + (e & 3) * 4;
#pragma unroll
          for (int k = 0; k < 3; k++) { const uint32_t hb = pack_bf16(v0, v1); sts32(ca + k * 16, hb); v0 -= bf_lo(hb); v1 -= bf_hi(hb); }
        }
        fence_async_smem();
        __syncwarp();
        if (lane == 0) { mbar_arrive(BAR(B_EPI1)); if (warp == 1) TSTAMP(8); }
      }
      if (tid == 96) {
        poll_ge(&g_cnt[CNT_LN * 32], ep1 * 128u);
        TSTAMP(9);
        asm volatile("fence.proxy.async.global;" ::: "memory");
        mbar_wait(BAR(B_KC), 0);
#pragma unroll
        for (int c = 0; c < 2; c++) {
          mbar_expect_tx(BAR(B_UF + c), 4096);
#pragma unroll
          for (int i = 0; i < 2; i++)
            bulk_ld(sb + OFF_CB + c * CBS + CB_U + i * U_JS, g_xnT + (size_t)(bid * 4 + c) * SEQ + i * 1024, 2048, BAR(B_UF + c));
        }
        TSTAMP(11);
      }
      __syncwarp();
      bar_sync(7 + warp, 288);
      if (lane == 0) {
        tma_st3d(&mHst, 64 * (warp - 1), nt, mt1 * 128, sb + (warp == 1 ? h_slot(0) : warp == 2 ? h_slot(1) : h_slot(2)));
        bulk_commit();
        if (warp == 3) TSTAMP(22);
        bulk_wait_read0(); mbar_arrive(BAR(B_STG));
        bulk_wait0();
        red_relaxed(&g_cnt[(CNT_H + mt1) * 32 + 16 * (nt >> 2)]);
        if (warp == 3) TSTAMP(28);
      }
      __syncwarp();
      if (warp != 2) {
#pragma unroll 1
        for (int c = 0; c < 2; c++) {
          mbar_wait(BAR(B_CF + c), 0);
          const int j = 128 + 16 * (warp - 1) + lane;
          if (j < 164) build_tap_task(j, sb + OFF_R + c * RCH, sb + OFF_CB + c * CBS);
          fence_async_smem();
          __syncwarp();
          if (lane == 0) mbar_arrive(BAR(B_TB + 1 + c));
        }
      }
      if (tid == 64) {
        mbar_wait(BAR(B_CD + 2), 0);
        poll_ge(&g_cnt[(CNT_S + 2 * dp + rank) * 32], ep1 * 128u);
        TSTAMP(33);
        mbar_wait(BAR(B_REL2 + 5), 0);
        TSTAMP(6);
        mbar_expect_tx(BAR(B_SF), SLOT);
        tma3d(sb + OFF_ST, &mS, (120 - 8 * mt2) * 8, dp * 128 + 64 * rank, 0, BAR(B_SF));
      }
    }
  } else if (role == 1) {
    asm volatile("setmaxnreg.dec.sync.aligned.u32 " STR(REG_AUX) ";");
    ROLE_IDS();
    const int t = tid - 128, w = warp - 4;
    {
      const int al = bid >> 1, jl = bid & 1, hf = t & 1;
      const int row0 = 32 * al + 8 * jl;
      uint4 raw[8];
      {
        const uint4* xp = reinterpret_cast<const uint4*>(P.x + (size_t)(row0 + hf * 16) * DM) + (t >> 1);
#pragma unroll
        for (int r = 0; r < 8; r++) raw[r] = __ldg(xp + r * (DM / 8));
      }
      const uint32_t red = sb + OFF_RED;
      float mu[8], m2[8];
#pragma unroll
      for (int r = 0; r < 8; r++) {
        const float x0 = bf_lo(raw[r].x), x1 = bf_hi(raw[r].x), x2 = bf_lo(raw[r].y), x3 = bf_hi(raw[r].y);
        const float x4 = bf_lo(raw[r].z), x5 = bf_hi(raw[r].z), x6 = bf_lo(raw[r].w), x7 = bf_hi(raw[r].w);
        const float m = (((x0 + x1) + (x2 + x3)) + ((x4 + x5) + (x6 + x7))) * 0.125f;
        const float d0 = x0 - m, d1 = x1 - m, d2 = x2 - m, d3 = x3 - m, d4 = x4 - m, d5 = x5 - m, d6 = x6 - m, d7 = x7 - m;
        mu[r] = m;
        m2[r] = (fmaf(d0, d0, d1 * d1) + fmaf(d2, d2, d3 * d3)) + (fmaf(d4, d4, d5 * d5) + fmaf(d6, d6, d7 * d7));
      }
      if (t == 0) TSTAMP(50);
      auto level = [&](int i, int j, int msk, float nh) {
        const bool up = lane & msk;
        const float om = __shfl_xor_sync(~0u, up ? mu[i] : mu[j], msk), oq = __shfl_xor_sync(~0u, up ? m2[i] : m2[j], msk);
        const float km = up ? mu[j] : mu[i], kq = up ? m2[j] : m2[i];
        const float d = km - om;
        mu[i] = 0.5f * (km + om);
        m2[i] = fmaf(d * d, nh, kq + oq);
      };
#pragma unroll
      for (int i = 0; i < 4; i++) level(i, i + 4, 16, 4.f);
#pragma unroll
      for (int i = 0; i < 2; i++) level(i, i + 2, 8, 8.f);
      level(0, 1, 4, 16.f);
      level(0, 0, 2, 32.f);
      if (!(lane & 2)) sts64(red + (hf * 8 + (lane >> 2)) * 32 + w * 8, __float_as_uint(mu[0]), __float_as_uint(m2[0]));
      bar_sync(1, 128);
      if (t < 16) {
        const uint4 p4 = lds128(red + t * 32), q4 = lds128(red + t * 32 + 16);
        const float ma = __uint_as_float(p4.x), mb2 = __uint_as_float(p4.z), mc = __uint_as_float(q4.x), md = __uint_as_float(q4.z);
        const float m01 = 0.5f * (ma + mb2), m23 = 0.5f * (mc + md);
        const float q01 = fmaf((ma - mb2) * (ma - mb2), 64.f, __uint_as_float(p4.y) + __uint_as_float(p4.w));
        const float q23 = fmaf((mc - md) * (mc - md), 64.f, __uint_as_float(q4.y) + __uint_as_float(q4.w));
        const float mean = 0.5f * (m01 + m23);
        const float var = fmaf((m01 - m23) * (m01 - m23), 128.f, q01 + q23) * (1.f / DM);
        const float mb = bf_round(mean);
        const float den = bf_round(sqrtf(bf_round(bf_round(var) + 1e-5f)));
        const float ri = 1.f / den;
        sts64(red + 512 + t * 8, pack_bf16(mb, mb), __float_as_uint(ri));
        mbar_wait(BAR(B_EPOCH), 0);
        st_tag(&g_stats[row0 + (t >> 3) * 16 + (t & 7)], __float_as_uint(ri), __float_as_uint(mb) | (lds32(sb + OFF_EPOCH) & 0xFFFFu));
      }
      bar_sync(1, 128);
      if (t == 0) TSTAMP(54);
      uint32_t o[8][4];
#pragma unroll
      for (int i = 0; i < 4; i++) {
        const uint4 st = lds128(red + 512 + hf * 64 + i * 16);
        const float fa = __uint_as_float(st.y), fb = __uint_as_float(st.w);
#pragma unroll
        for (int k = 0; k < 4; k++) {
          const uint32_t xa = k == 0 ? raw[2 * i].x : k == 1 ? raw[2 * i].y : k == 2 ? raw[2 * i].z : raw[2 * i].w;
          const uint32_t xb = k == 0 ? raw[2 * i + 1].x : k == 1 ? raw[2 * i + 1].y : k == 2 ? raw[2 * i + 1].z : raw[2 * i + 1].w;
          const uint32_t a0 = hsub2_bf(xa, st.x), b0 = hsub2_bf(xb, st.z);
          o[2 * k][i] = pack_bf16(bf_lo(a0) * fa, bf_lo(b0) * fb);
          o[2 * k + 1][i] = pack_bf16(bf_hi(a0) * fa, bf_hi(b0) * fb);
        }
      }
      __nv_bfloat16* dst = g_xnT + (size_t)(8 * (t >> 1)) * SEQ + jl * 1024 + (127 - hf - 2 * al) * 8;
#pragma unroll
      for (int j = 0; j < 8; j++) *reinterpret_cast<uint4*>(dst + j * SEQ) = make_uint4(o[j][0], o[j][1], o[j][2], o[j][3]);
      if (t == 0) TSTAMP(55);
    }
    mbar_wait(BAR(B_KG), 0);
    {
      const uint32_t kc = sb + OFF_KC + w * KG_TAB, rb = sb + OFF_R + (w ^ 2) * RCH;
      const uint32_t pb = sb + OFF_CB + 4 * w * KG_TAB + lane * 16;
      const int g = lane >> 2, q = lane & 3;
#pragma unroll 2
      for (int it = 0; it < 6; it++) {
        const uint4 p0 = lds128(pb + it * 512), p1 = lds128(pb + KG_TAB + it * 512), p2 = lds128(pb + 2 * KG_TAB + it * 512), p3 = lds128(pb + 3 * KG_TAB + it * 512);
        auto s4 = [](uint32_t a, uint32_t b2, uint32_t c, uint32_t d) { return (__uint_as_float(a) + __uint_as_float(b2)) + (__uint_as_float(c) + __uint_as_float(d)); };
        const uint32_t lo = pack_bf16(s4(p0.x, p1.x, p2.x, p3.x), s4(p0.y, p1.y, p2.y, p3.y));
        const uint32_t hi = pack_bf16(s4(p0.z, p1.z, p2.z, p3.z), s4(p0.w, p1.w, p2.w, p3.w));
        const int jt = it >= 3 ? it - 3 : it, j = g + (it >= 3 ? 16 : 0);
        if (jt < 2) {
          const int stp = jt == 0 ? 8 : q < 2 ? 4 : 2;
          const int i0 = (jt == 0 ? 2 * q : q < 2 ? 256 + 2 * q : 384 + 64 * (q - 2)) + stp * j;
          sts32(kc + i0 * 2, lo); sts32(kc + (i0 + 8 * stp) * 2, hi);
        } else if (q < 2) {
          const uint32_t a0 = kc + (512 + 64 * q + j) * 2;
          sts16(a0, lo); sts16(a0 + 64, lo >> 16); sts16(a0 + 16, hi); sts16(a0 + 80, hi >> 16);
        } else if (q == 2 && j == 0) sts16(kc + 1280, lo);
      }
      bar_sync(1, 128);
      if (t == 0) mbar_arrive(BAR(B_KC));
      if (t == 96) { red_release(&g_cnt[CNT_LN * 32]); TSTAMP(10); }
      __syncwarp();
      const uint4 c0 = lds128(kc + lane * 16);
      const uint2 c1 = lds64(kc + 512 + lane * 8);
      const uint32_t c1n = lds32(kc + 520 + lane * 8);
      const uint32_t c2 = lds32(kc + 768 + lane * 4), c2n = lds32(kc + 772 + lane * 4);
      const uint32_t c3 = lds32(kc + 896 + lane * 4), c3n = lds32(kc + 900 + lane * 4);
      const uint4 f0 = lds128(kc + 1024 + (lane & 7) * 32), f1 = lds128(kc + 1040 + (lane & 7) * 32);
      const uint32_t f2 = lds32(kc + 1056 + (lane & 7) * 32);
      const uint32_t ra = rb + (35 - lane) * 16;
      sts128(ra, __byte_perm(c0.w, 0, 0x1032), __byte_perm(c0.z, 0, 0x1032), __byte_perm(c0.y, 0, 0x1032), __byte_perm(c0.x, 0, 0x1032));
      sts128(ra + 608, __byte_perm(c1n, c1.y, 0x7610), __byte_perm(c1.y, 0, 0x1010), __byte_perm(c1.y, c1.x, 0x7610), __byte_perm(c1.x, 0, 0x1010));
      sts128(ra + 1216, __byte_perm(c2n, 0, 0x1010), __byte_perm(c2, 0, 0x3232), __byte_perm(c2, 0, 0x1032), __byte_perm(c2, 0, 0x1010));
      sts128(ra + 1824, __byte_perm(c3n, 0, 0x1010), __byte_perm(c3, 0, 0x3232), __byte_perm(c3, 0, 0x1032), __byte_perm(c3, 0, 0x1010));
      {
        const uint32_t k1024 = __shfl_sync(~0u, f0.x, 0);
        const int h = lane / 6, r = lane - 6 * h;
        const uint32_t kk = lane == 21 ? __byte_perm(k1024, 0, 0x1010) : 0u;
        const uint32_t za = lane < 24 ? rb + h * 608 + (r < 4 ? r : 32 + r) * 16 : rb + 2432 + ((lane >> 1) & 1) * 160 + 128 + (lane & 1) * 16;
        if (lane < 28) sts128(za, 0, kk & 0xFFFF0000u, kk, kk);
      }
      if (lane < 16) {
        const bool ev = lane >= 8;
        const uint32_t o0 = ev ? __byte_perm(f2, f1.w, 0x5410) : __byte_perm(f1.w, f1.z, 0x7632);
        const uint32_t o1 = ev ? __byte_perm(f1.z, f1.y, 0x5410) : __byte_perm(f1.y, f1.x, 0x7632);
        const uint32_t o2 = ev ? __byte_perm(f1.x, f0.w, 0x5410) : __byte_perm(f0.w, f0.z, 0x7632);
        const uint32_t o3 = ev ? __byte_perm(f0.z, f0.y, 0x5410) : __byte_perm(f0.y, f0.x, 0x7632);
        sts128(rb + 2432 + (lane >> 3) * 160 + (7 - (lane & 7)) * 16, o0, o1, o2, o3);
      }
    }
    bar_sync(1, 128);
    if (t == 0) TSTAMP(58);
    if (t < 68) {
      const int jj = t / 17;
      sts128(sb + OFF_CB + (jj >> 1) * CBS + CB_U + (jj & 1) * U_JS + (128 + t - 17 * jj) * 16, 0, 0, 0, 0);
    }
    if (t < 81) { sts128(sb + OFF_CB + 1152 + t * 16, 0, 0, 0, 0); sts128(sb + OFF_CB + CBS + 1152 + t * 16, 0, 0, 0, 0); }
    bar_sync(1, 128);
    mbar_wait(BAR(B_G1E), 0);
#pragma unroll 1
    for (int c = 0; c < 4; c++) {
      const uint32_t cb = sb + OFF_CB + (c & 1) * CBS;
      if (c >= 2) {
        mbar_wait(BAR(B_CF + c - 2), 0);
        if (t == 0) {
          mbar_expect_tx(BAR(B_UF + c), 4096);
#pragma unroll
          for (int i = 0; i < 2; i++) bulk_ld(cb + CB_U + i * U_JS, g_xnT + (size_t)(bid * 4 + c) * SEQ + i * 1024, 2048, BAR(B_UF + c));
        }
        __syncwarp();
      }
#pragma unroll 1
      for (int j = t; j < (c < 2 ? 164 : 128); j += 128) build_tap_task(j, sb + OFF_R + (c ^ 2) * RCH, cb);
      if (c >= 2) {
        fence_async_smem();
        __syncwarp();
        if (lane == 0) mbar_arrive(BAR(B_TB + c - 1));
      }
      __syncwarp();
#pragma unroll 1
      for (int z = (c == 1 ? 0 : c); z <= c && c > 0; z++) {
        mbar_wait(BAR(B_UF + z), 0);
        build_z(sb + OFF_CB + (z & 1) * CBS, w, lane);
      }
      if (c > 0) {
        fence_async_smem();
        __syncwarp();
        if (lane == 0) mbar_arrive(BAR(c == 1 ? B_TB : B_TZ + c - 2));
        if (t == 0) TSTAMP(12 + c);
      }
    }
  } else {
    asm volatile("setmaxnreg.inc.sync.aligned.u32 " STR(REG_CONS) ";");
    ROLE_IDS();
    if (tid == 256) TSTAMP(42);
    const int wg = (warp >> 2) - 2, w = warp & 3, g = lane >> 2;
    const bool el = (tid & 127) == 0;
    const int rr = (lane & 7) + ((lane >> 3) & 1) * 8;
    {
      const uint32_t e_bar = mapa(BAR(B_EMPTYB), rank ^ (w & 1));
      const uint32_t xcnt = (wg == 0 && P.nhelp) ? 4u : 1u;
      float acc[176];
      const uint64_t dA = make_desc(SB0 + OFF_A + wg * 8192, 16, 1024, 1);
      const uint64_t dB = make_desc(SB0 + OFF_B, 4096, 1024, 1);
      auto release = [&](int hb) {
        if (lane == 0) {
          if (w < 2) mbar_arrive_n(e_bar + 8 * (hb & 3), hb >= KSPLIT / 32 ? xcnt : 1u);
          else if (w == 2 && (hb & 1)) mbar_arrive(BAR(B_EMPTYA + (hb >> 1) % 3));
        }
        __syncwarp();
      };
#pragma unroll
      for (int hb = 0; hb < 16; hb++) {
        const int kb = hb >> 1, sa = kb % 3, sbi = hb & 3;
        if (!(hb & 1)) mbar_wait(BAR(B_FULLA + sa), (kb / 3) & 1);
        mbar_wait(BAR(B_FULLB + sbi), (hb >> 2) & 1);
        if (hb == 0 && el && wg == 0) TSTAMP(24);
        wgmma_fence();
#pragma unroll
        for (int k = 0; k < 2; k++) {
          const uint64_t da = dA + (uint64_t)((sa * SLOT + (hb & 1) * 64 + k * 32) >> 4);
          const uint64_t db = dB + (uint64_t)((sbi * BST + k * 2048) >> 4);
          const int sc = (hb | k) != 0;
          wgmma_n176_ss<0, 1>(acc, da, db, sc);
          wgmma_n176_ss<0, 1>(acc + 88, da, db + (12288 >> 4), sc);
        }
        wgmma_commit();
        wgmma_wait<1>();
        if (hb > 0) release(hb - 1);
        if (hb == TAB_LATE && lane == 0 && wg == 0) mbar_arrive(BAR(B_G1E));
      }
      if (el && wg == 0) TSTAMP(23);
      mbar_wait(BAR(B_EPI1), 0);
      {
        const uint64_t dm = make_desc(SB0 + OFF_MA + wg * 1024, 0, 128, 0), dc = make_desc(SB0 + OFF_CS, 0, 48, 0);
        wgmma_fence();
        wgmma_n176_ss<0, 1>(acc, dm, dc, 1);
        wgmma_n176_ss<0, 1>(acc + 88, dm, dc + ((22 * 48) >> 4), 1);
        wgmma_commit();
      }
      const int r0 = wg * 64 + w * 16 + g;
      float rh0 = __uint_as_float(lds32(sb + OFF_STAT + r0 * 4)), rh1 = __uint_as_float(lds32(sb + OFF_STAT + (r0 + 8) * 4));
      wgmma_wait<0>();
      fence_regs<176>(acc);
      if (el) TSTAMP(wg ? 26 : 25);
      bar_sync(2, 256);
      const uint32_t stg = sb + (wg * 4 + w) * 2048;
      const uint32_t sta = stg + rr * 128;
#pragma unroll
      for (int n = 0; n < 22; n += 2) {
        uint32_t hp[4];
#pragma unroll
        for (int i = 0; i < 2; i++) {
          const float* ag = acc + 4 * (n + i);
          const float* au = ag + 88;
          const float u00 = au[0] * rh0, u01 = au[1] * rh0, u10 = au[2] * rh1, u11 = au[3] * rh1;
          hp[2 * i] = pack_bf16(fmaf(u00, tanhaf(ag[0] * rh0), u00), fmaf(u01, tanhaf(ag[1] * rh0), u01));
          hp[2 * i + 1] = pack_bf16(fmaf(u10, tanhaf(ag[2] * rh1), u10), fmaf(u11, tanhaf(ag[3] * rh1), u11));
        }
        stsm4(sta + h_slot(n >> 3) + ((((n & 7) + (lane >> 4)) ^ (rr & 7)) << 4), hp[0], hp[1], hp[2], hp[3]);
        if (n == 6 || n == 14 || n == 20) {
          fence_async_smem();
          asm volatile("bar.arrive %0, 288;" ::"r"(8 + (n >> 3)) : "memory");
          if (n < 20) { rh0 = __uint_as_float(lds32(sb + OFF_STAT + r0 * 4)); rh1 = __uint_as_float(lds32(sb + OFF_STAT + (r0 + 8) * 4)); }
        }
      }
      if (el) TSTAMP(wg ? 21 : 27);
    }
    uint32_t xv[16], sv[16];
    const uint32_t xw = sb + OFF_XT + (wg * 64 + w * 16) * 128, xa = xw + rr * 128;
    auto load_xs = [&]() {
      mbar_wait(BAR(B_XF), 0); mbar_wait(BAR(B_SF), 0);
      const int ap = 7 - (4 * wg + w);
#pragma unroll
      for (int i = 0; i < 8; i += 2) {
        const int ti = i + (lane >> 4);
        ldsm4(xv + 2 * i, xa + ((ti ^ (rr & 7)) << 4));
        ldsm4t(sv + 2 * i, sb + OFF_ST + ((lane >> 3) & 1) * 8192 + (8 * ti + (lane & 7)) * 128 + ((ap ^ (lane & 7)) << 4));
      }
    };
    float o[32];
    const bool odd = w & 1;
    const uint2 dk4 = __ldg(reinterpret_cast<const uint2*>(P.dskip + bid * 4));
    auto issue = [&](float* acc, uint32_t* uu, int c) {
      const uint32_t cb = sb + OFF_CB + (c & 1) * CBS;
      mbar_wait(BAR(B_TB + (c < 2 ? 0 : c - 1)), 0);
      if (c >= 2) mbar_wait(BAR(B_UF + c), 0);
      if (el) TSTAMP(c == 3 ? 30 : c == 2 ? 31 : 29);
      wgmma_fence();
      const uint64_t da = make_desc(SB0 + OFF_CB + (c & 1) * CBS + CB_H, 576, 144, 0), db = make_desc(SB0 + OFF_CB + (c & 1) * CBS + CB_U, U_JS, 128, 0);
#pragma unroll
      for (int dl = 0; dl < 18; dl++) wgmma_n128_ss<0, 0>(acc, da + (uint64_t)(((34 - 2 * dl) * 576) >> 4), db + (uint64_t)dl, dl != 0);
      mbar_wait(BAR(c >= 2 ? B_TZ + c - 2 : B_TB), 0);
      wgmma_fence();
#pragma unroll
      for (int f = 0; f < 2; f++)
        wgmma_n128_ss<1, 0>(acc, make_desc(SB0 + OFF_CB + (c & 1) * CBS + CB_Z + f * 2048, 128, 256, 0), make_desc(SB0 + OFF_CB + (c & 1) * CBS + CB_B3 + f * 2448, 144, 144, 0), 1);
      wgmma_commit();
      const uint32_t ub = cb + CB_U + (1 - (w >> 1)) * U_JS + (odd ? 0 : 1024);
      ldsm4t(uu, ub + lane * 16);
      ldsm4t(uu + 4, ub + 512 + lane * 16);
    };
    auto finish = [&](float* acc, const uint32_t* uu, int c) {
      if (lane == 0) bulk_wait_read0();
      const uint32_t dk = __byte_perm((c & 2) ? dk4.y : dk4.x, 0, (c & 1) ? 0x3232 : 0x1010);
      float y[16];
      const uint32_t xb = sb + (c == 1 ? OFF_CB + CBS + CB_H : OFF_CX) + (w >> 1) * 3072 + lane * 16;
      if (c == 1) bar_sync(4, 128);
      else __syncwarp();
      if (odd) {
#pragma unroll
        for (int k = 0; k < 8; k++) { y[2 * k] = acc[4 * (k + 4)] + acc[4 * (k + 6) + 2]; y[2 * k + 1] = acc[4 * (k + 4) + 1] + acc[4 * (k + 6) + 3]; }
        sts128(xb + 2048, __float_as_uint(acc[48] + acc[58]), __float_as_uint(acc[49] + acc[59]), __float_as_uint(acc[52] + acc[62]), __float_as_uint(acc[53] + acc[63]));
        sts128(xb + 2560, __float_as_uint(acc[56]), __float_as_uint(acc[57]), __float_as_uint(acc[60]), __float_as_uint(acc[61]));
      } else {
#pragma unroll
        for (int k = 0; k < 8; k += 2)
          sts128(xb + k * 256, __float_as_uint(acc[4 * k] + acc[4 * k + 10]), __float_as_uint(acc[4 * k + 1] + acc[4 * k + 11]),
                 __float_as_uint(acc[4 * k + 4] + acc[4 * k + 14]), __float_as_uint(acc[4 * k + 5] + acc[4 * k + 15]));
#pragma unroll
        for (int k = 8; k < 16; k++) {
          y[2 * (k - 8)] = acc[4 * k] + (k < 14 ? acc[4 * k + 10] : 0.f);
          y[2 * (k - 8) + 1] = acc[4 * k + 1] + (k < 14 ? acc[4 * k + 11] : 0.f);
        }
      }
      if (c == 1) bar_sync(4, 128); else bar_sync(5 + (w >> 1), 64);
#pragma unroll
      for (int k = 0; k < 4; k++) {
        if (odd || k < 2) {
          const uint4 v = lds128(xb + (odd ? 0 : 2048) + k * 512);
          y[4 * k] += __uint_as_float(v.x); y[4 * k + 1] += __uint_as_float(v.y); y[4 * k + 2] += __uint_as_float(v.z); y[4 * k + 3] += __uint_as_float(v.w);
        }
      }
      uint32_t sv[8];
#pragma unroll
      for (int i = 0; i < 8; i++) sv[i] = hadd2_bf(pack_bf16(y[2 * i], y[2 * i + 1]), hmul2_bf(uu[i], dk));
      const uint32_t stg = sb + (c == 1 ? OFF_CB + CBS + CB_Z : OFF_CS2) + w * 1024;
      stsm4t(stg + lane * 16, sv[0], sv[1], sv[2], sv[3]);
      stsm4t(stg + 512 + lane * 16, sv[4], sv[5], sv[6], sv[7]);
      fence_async_smem();
      __syncwarp();
      if (lane == 0) {
        bulk_st(g_sT + (size_t)(bid * 4 + c) * SEQ + (1 - (w >> 1)) * 1024 + (odd ? 0 : 512), stg, 1024);
        bulk_commit();
        if (w == 0) TSTAMP(16 + c);
      }
      __syncwarp();
    };
    if (wg == 0) {
      {
        float acc[64];
        uint32_t uu[8];
        mbar_wait(BAR(B_CD), 0);
        issue(acc, uu, 1);
        wgmma_wait<0>(); fence_regs<64>(acc);
        finish(acc, uu, 1);
        if (lane == 0) { bulk_wait_read0(); mbar_arrive(BAR(B_CF + 1)); }
        __syncwarp();
      }
      float acc[128];
      const uint64_t dA = make_desc(SB0, 16, 1024, 1);
      const uint64_t dB = make_desc(SB0, 8192, 1024, 1);
      const uint32_t xr = mapa(BAR(B_XCR), rank ^ 1), tf = mapa(BAR(B_TF), 0);
#pragma unroll
      for (int i = 0; i < 9; i++) {
        if (i == 1) { if (lane == 0) { bulk_wait0(); red_relaxed(&g_cnt[(CNT_S + (bid >> 4)) * 32]); } __syncwarp(); }
        if (i == G2_S1 || i == G2_S2) {
          wgmma_wait<0>();
          if (el) { mbar_arrive(BAR(B_REL2 + i - 1)); if (i == 5) mbar_arrive_remote(tf); if (i == 7) mbar_arrive_remote(xr); }
          mbar_wait(BAR(B_CD + 1 + (i == G2_S2)), 0);
        }
        mbar_wait(BAR(B_FULL2 + i), 0);
        if (el && i == 0) TSTAMP(32);
        wgmma_fence();
#pragma unroll
        for (int k = 0; k < 4; k++) {
          const uint64_t da = dA + (uint64_t)((h_slot(i) + k * 32) >> 4), db = dB + (uint64_t)((wd_slot(i) + k * 2048) >> 4);
          wgmma_n128_ss<0, 1>(acc, da, db, (i | k) != 0);
          wgmma_n128_ss<0, 1>(acc + 64, da + (8192 >> 4), db, (i | k) != 0);
        }
        wgmma_commit();
        wgmma_wait<1>();
        if (i > 0 && i < 8 && i != G2_S1 && i != G2_S2 && el) { mbar_arrive(BAR(B_REL2 + i - 1)); if (i == 5) mbar_arrive_remote(tf); if (i == 7) mbar_arrive_remote(xr); }
      }
      mbar_wait(BAR(B_XCR), 0);
      mbar_wait(BAR(B_FULL2 + 9), 0);
      wgmma_wait<0>();
      fence_regs<128>(acc);
      if (el) TSTAMP(43);
      const uint32_t rdst = mapa(sb + OFF_XC + w * 4096 + lane * 16, rank ^ 1), rbar = mapa(BAR(B_XCF), rank ^ 1);
      uint32_t pk[32];
#pragma unroll
      for (int i = 0; i < 32; i++) { const float* a = acc + (i < 16 ? 32 + 2 * i : 64 + 2 * i); pk[i] = pack_bf16(a[0], a[1]); }
#pragma unroll
      for (int i = 9; i < 13; i++) {
        if (i > 9) mbar_wait(BAR(B_FULL2 + i), 0);
        wgmma_fence();
#pragma unroll
        for (int k = 0; k < (i < 12 ? 4 : 2); k++) {
          const uint64_t da = dA + (uint64_t)((h_slot(i) + k * 32) >> 4), db = dB + (uint64_t)((wd_slot(i) + k * 2048) >> 4);
          wgmma_n64_ss<0, 1>(acc, da, db, 1);
          wgmma_n64_ss<0, 1>(acc + 64, da + (8192 >> 4), db, 1);
        }
        wgmma_commit();
        if (i == 9) {
#pragma unroll
          for (int j = 0; j < 8; j++)
            asm volatile("st.async.weak.shared::cluster.mbarrier::complete_tx::bytes.v4.b32 [%0], {%1,%2,%3,%4}, [%5];"
                         ::"r"(rdst + j * 512), "r"(pk[4 * j]), "r"(pk[4 * j + 1]), "r"(pk[4 * j + 2]), "r"(pk[4 * j + 3]), "r"(rbar) : "memory");
          if (el) TSTAMP(52);
        }
      }
      load_xs();
      if (el) TSTAMP(45);
      wgmma_wait<0>();
      fence_regs<32>(acc); fence_regs<32>(acc + 64);
      if (el) TSTAMP(44);
#pragma unroll
      for (int i = 0; i < 8; i++)
        sts128(sb + OFF_XL + (tid & 127) * 16 + i * 2048, __float_as_uint(acc[64 + 4 * i]), __float_as_uint(acc[65 + 4 * i]),
               __float_as_uint(acc[66 + 4 * i]), __float_as_uint(acc[67 + 4 * i]));
      __syncwarp();
      if (lane == 0) mbar_arrive(BAR(B_XCL));
      if (el) TSTAMP(53);
#pragma unroll
      for (int i = 0; i < 32; i++) o[i] = acc[i];
    } else {
#pragma unroll
      for (int ci = 0; ci < 3; ci++) {
        const int c = ci + (ci > 0);
        float acc[64];
        uint32_t uu[8];
        issue(acc, uu, c);
        if (el) mbar_arrive(BAR(B_CD + ci));
        wgmma_wait<0>(); fence_regs<64>(acc);
        asm volatile("" ::"r"(uu[0]), "r"(uu[4]) : "memory");
        if (lane == 0) { if (c < 3) mbar_arrive(BAR(B_CF + c)); else mbar_arrive_remote(mapa(BAR(B_CF3), 1)); }
        finish(acc, uu, c);
      }
      if (lane == 0) { bulk_wait0(); red_relaxed(&g_cnt[(CNT_S + (bid >> 4)) * 32]); if (w == 0) TSTAMP(20); }
      __syncwarp();
    }
#pragma unroll 1
    for (int pass = 1 - wg; pass < 2; pass++) {
      if (wg) {
        if (pass) { load_xs(); mbar_wait(BAR(B_XCL), 0); }
#pragma unroll
        for (int i = 0; i < 8; i++) {
          const uint4 v = lds128(sb + OFF_XL + (tid & 127) * 16 + i * 2048);
          o[4 * i] = __uint_as_float(v.x); o[4 * i + 1] = __uint_as_float(v.y); o[4 * i + 2] = __uint_as_float(v.z); o[4 * i + 3] = __uint_as_float(v.w);
        }
      }
      if (pass) mbar_wait_cluster(BAR(B_XCF), 0);
      if (el && wg == 0) TSTAMP(46);
      uint32_t ov[16], pr[16];
#pragma unroll
      for (int i = 0; i < 4; i++) {
        const uint4 v = lds128(sb + OFF_XC + w * 4096 + wg * 2048 + i * 512 + lane * 16);
        pr[4 * i] = v.x; pr[4 * i + 1] = v.y; pr[4 * i + 2] = v.z; pr[4 * i + 3] = v.w;
      }
#pragma unroll
      for (int i = 0; i < 8; i++) {
        const uint32_t o01 = pack_bf16(o[4 * i] + bf_lo(pr[2 * i]), o[4 * i + 1] + bf_hi(pr[2 * i]));
        const uint32_t o23 = pack_bf16(o[4 * i + 2] + bf_lo(pr[2 * i + 1]), o[4 * i + 3] + bf_hi(pr[2 * i + 1]));
        auto silu = [](float v) { const float hf = 0.5f * v; return fmaf(hf, tanhaf(hf), hf); };
        const uint32_t g01 = pack_bf16(silu(bf_lo(o01)), silu(bf_hi(o01)));
        const uint32_t g23 = pack_bf16(silu(bf_lo(o23)), silu(bf_hi(o23)));
        ov[2 * i] = hadd2_bf(xv[2 * i], hmul2_bf(sv[2 * i], g01));
        ov[2 * i + 1] = hadd2_bf(xv[2 * i + 1], hmul2_bf(sv[2 * i + 1], g23));
      }
      if (pass) {
#pragma unroll
        for (int i = 0; i < 8; i += 2) stsm4(xa + (((i + (lane >> 4)) ^ (rr & 7)) << 4), ov[2 * i], ov[2 * i + 1], ov[2 * i + 2], ov[2 * i + 3]);
        __syncwarp();
        __nv_bfloat16* dst = P.out + (size_t)(mt2 * 128 + wg * 64 + w * 16 + (lane >> 3)) * DM + dp * 128 + 64 * rank + (lane & 7) * 8;
#pragma unroll
        for (int i = 0; i < 4; i++) {
          const int r = 4 * i + (lane >> 3);
          *reinterpret_cast<uint4*>(dst + 4 * i * DM) = lds128(xw + r * 128 + (((lane & 7) ^ (r & 7)) << 4));
        }
        if (el && wg == 0) TSTAMP(47);
      } else if (ov[0] == 0x12345678u && ov[5] == 0x9abcdef0u && (ov[1] ^ ov[2] ^ ov[3] ^ ov[4] ^ ov[6] ^ ov[7] ^ ov[8] ^ ov[9] ^ ov[10] ^ ov[11] ^ ov[12] ^ ov[13] ^ ov[14] ^ ov[15]) == 1u) {
        sts32(sb + OFF_EPOCH + 4, 0);
      }
    }
    {
    }
  }
#undef BAR
}

typedef CUresult (*EncodeFn)(CUtensorMap*, CUtensorMapDataType, cuuint32_t, void*, const cuuint64_t*, const cuuint64_t*, const cuuint32_t*,
                             const cuuint32_t*, CUtensorMapInterleave, CUtensorMapSwizzle, CUtensorMapL2promotion, CUtensorMapFloatOOBfill);

void make_map(EncodeFn enc, CUtensorMap* m, const void* base, int rank, const cuuint64_t* dims, const cuuint64_t* strides, const cuuint32_t* box,
              CUtensorMapSwizzle swz) {
  const cuuint32_t es[3] = {1, 1, 1};
  enc(m, CU_TENSOR_MAP_DATA_TYPE_BFLOAT16, rank, const_cast<void*>(base), dims, strides, box, es, CU_TENSOR_MAP_INTERLEAVE_NONE, swz,
      CU_TENSOR_MAP_L2_PROMOTION_L2_128B, CU_TENSOR_MAP_FLOAT_OOB_FILL_NONE);
}

}

extern "C" void kernel_launch(void* const* d_in, const int* in_sizes, int n_in, void* d_out, int out_size) {
  (void)in_sizes; (void)n_in; (void)out_size;
  static EncodeFn enc = nullptr;
  static void *p_h = nullptr, *p_s = nullptr;
  static int nhelp = 0;
  if (!enc) {
    void* fn = nullptr;
    cudaDriverEntryPointQueryResult qr;
    cudaGetDriverEntryPoint("cuTensorMapEncodeTiled", &fn, cudaEnableDefault, &qr);
    enc = (EncodeFn)fn;
    cudaGetSymbolAddress(&p_h, g_h);
    cudaGetSymbolAddress(&p_s, g_sT);
    cudaFuncSetAttribute(fused_kernel, cudaFuncAttributeMaxDynamicSharedMemorySize, SMEM_BYTES);
    cudaLaunchConfig_t cfg = {};
    cfg.gridDim = dim3(132); cfg.blockDim = dim3(512); cfg.dynamicSmemBytes = SMEM_BYTES;
    cudaLaunchAttribute at[1];
    at[0].id = cudaLaunchAttributeClusterDimension; at[0].val.clusterDim.x = 2; at[0].val.clusterDim.y = 1; at[0].val.clusterDim.z = 1;
    cfg.attrs = at; cfg.numAttrs = 1;
    int nc = 0;
    if (cudaOccupancyMaxActiveClusters(&nc, fused_kernel, &cfg) == cudaSuccess && nc >= 66) nhelp = 4;
    (void)cudaGetLastError();
  }
  typedef const __nv_bfloat16* bp;
  CUtensorMap mX, mWg, mWu, mHst, mHld, mWd, mS, mWg48, mWu48, mH32, mWd32;
  { cuuint64_t d[2] = {DM, SEQ}, s[1] = {DM * 2}; cuuint32_t b[2] = {64, 128}; make_map(enc, &mX, d_in[0], 2, d, s, b, CU_TENSOR_MAP_SWIZZLE_128B); }
  { cuuint64_t d[2] = {FF, DM}, s[1] = {FF * 2}; cuuint32_t b[2] = {64, 32};
    make_map(enc, &mWg, d_in[10], 2, d, s, b, CU_TENSOR_MAP_SWIZZLE_128B); make_map(enc, &mWu, d_in[11], 2, d, s, b, CU_TENSOR_MAP_SWIZZLE_128B);
    b[0] = 48;
    make_map(enc, &mWg48, d_in[10], 2, d, s, b, CU_TENSOR_MAP_SWIZZLE_128B); make_map(enc, &mWu48, d_in[11], 2, d, s, b, CU_TENSOR_MAP_SWIZZLE_128B); }
  { cuuint64_t d[3] = {176, 8, SEQ}, s[2] = {352, FP * 2}; cuuint32_t b[3] = {64, 1, 128}; make_map(enc, &mHst, p_h, 3, d, s, b, CU_TENSOR_MAP_SWIZZLE_128B); }
  { cuuint64_t d[2] = {FP, SEQ}, s[1] = {FP * 2}; cuuint32_t b[2] = {64, 128}; make_map(enc, &mHld, p_h, 2, d, s, b, CU_TENSOR_MAP_SWIZZLE_128B);
    b[0] = 32; make_map(enc, &mH32, p_h, 2, d, s, b, CU_TENSOR_MAP_SWIZZLE_128B); }
  { cuuint64_t d[2] = {DM, FF}, s[1] = {DM * 2}; cuuint32_t b[2] = {64, 64}; make_map(enc, &mWd, d_in[12], 2, d, s, b, CU_TENSOR_MAP_SWIZZLE_128B);
    b[1] = 32; make_map(enc, &mWd32, d_in[12], 2, d, s, b, CU_TENSOR_MAP_SWIZZLE_128B); }
  { cuuint64_t d[3] = {1024, DM, 2}, s[2] = {SEQ * 2, 2048}; cuuint32_t b[3] = {64, 64, 2}; make_map(enc, &mS, p_s, 3, d, s, b, CU_TENSOR_MAP_SWIZZLE_128B); }
  Params P;
  P.x = (bp)d_in[0]; P.Are = (bp)d_in[1]; P.Aim = (bp)d_in[2]; P.Bre = (bp)d_in[3]; P.Bim = (bp)d_in[4]; P.Cre = (bp)d_in[5];
  P.Cim = (bp)d_in[6]; P.logdt = (bp)d_in[7]; P.dskip = (bp)d_in[8]; P.wg = (bp)d_in[10]; P.wu = (bp)d_in[11]; P.wd = (bp)d_in[12];
  P.nhelp = nhelp; P.out = (__nv_bfloat16*)d_out;
  fused_kernel<<<128 + nhelp, 512, SMEM_BYTES, cudaStreamPerThread>>>(P, mX, mWg, mWu, mHst, mHld, mWd, mS, mWg48, mWu48, mH32, mWd32);
}
```
